```python
import torch

def _softmax(x, axis=-1):
    return torch.softmax(x, dim=axis)
def _gelu(x):
    return torch.nn.functional.gelu(x, approximate="tanh")
def _silu(x):
    return torch.nn.functional.silu(x)
def _sigmoid(x):
    return torch.sigmoid(x)
def _layernorm(x, axis=-1, eps=1e-5):
    m = x.mean(dim=axis, keepdim=True)
    v = x.var(dim=axis, keepdim=True, unbiased=False)
    return (x - m) / torch.sqrt(v + eps)
def _scatter_add(tgt, idx, src, axis=0):
    return tgt.clone().index_add_(axis, idx, src)
def _segment_sum(src, seg, n):
    out = torch.zeros((n,) + src.shape[1:], dtype=src.dtype)
    return out.index_add_(0, seg, src)
def _pad(x, pw):
    flat = tuple(v for pair in reversed(pw) for v in pair)
    return torch.nn.functional.pad(x, flat)

kernel_name = 'standalone__cross_network_dcn__recsys'

def setup_inputs():

    _w = (lambda a: (lambda t: t.to(torch.bfloat16) if t.is_floating_point() else t)(torch.as_tensor(a)))
    B, F, D, L = 16384, 26, 32, 3
    Din = min(F * D, 1024)
    return {
        "x0": _w((lambda *s: torch.randn(*s, dtype=torch.bfloat16) * 0.05)(B, Din)),
        "ws": _w((lambda *s: torch.randn(*s, dtype=torch.bfloat16) * 0.4)(L, Din, Din) * (Din ** -0.5)),
        "bs": _w((lambda *s: torch.randn(*s, dtype=torch.bfloat16) * 3.2)(L, Din) * 0.01),
    }

def reference(x0, ws, bs):
    x = x0
    L = ws.shape[0]
    for l in range(L):
        proj = torch.einsum('bd,de->be', x, ws[l]) + bs[l]
        x = x0 * proj + x
    return x
```

```cpp
#include <cuda_runtime.h>
#include <cuda_bf16.h>
#include <cuda.h>
#include <stdint.h>

#define OPT_X0PF 1
#define OPT_MC 0
#define OPT_PFD 3
#define OPT_PF0 1
#define OPT_W0 1
#define OPT_FS 11
#define OPT_KO 5
#define OPT_SNS 500
#define OPT_LEADS 0
#define OPT_LEAD 3

namespace {

constexpr int kB = 16384;
constexpr int kD = 832;
constexpr int kL = 3;
constexpr int kBM = 128;
constexpr int kNS = 8;
constexpr int kSlot = 16384;
constexpr int kNSC = 4;
constexpr int kNRC = 9;

constexpr uint32_t SB = 1024;
constexpr uint32_t RING = SB;
constexpr uint32_t WGB = RING + kNS * kSlot;
constexpr uint32_t kWgStride = (kNSC + 2) * 8192;
constexpr uint32_t SREG = WGB;
constexpr uint32_t STG = WGB + kNSC * 8192;
constexpr uint32_t BIAS = WGB + 2 * kWgStride;
constexpr uint32_t kBiasStride = 768;
constexpr uint32_t BAR_FULL = BIAS + 2 * kBiasStride;
constexpr uint32_t BAR_EMPTY = BAR_FULL + 8 * kNS;
constexpr uint32_t BAR_SFULL = BAR_EMPTY + 8 * kNS;
constexpr uint32_t BAR_SFREE = BAR_SFULL + 16;
constexpr uint32_t BAR_STGFULL = BAR_SFREE + 16;
constexpr uint32_t BAR_OUTRDY = BAR_STGFULL + 16;
constexpr uint32_t BAR_XREADY = BAR_OUTRDY + 16;
constexpr uint32_t BAR_SFULLC = BAR_XREADY + 32;
constexpr uint32_t SCHED = BAR_SFULLC + 32;
constexpr int kMaxRing = 288;
constexpr int kTiles = 21;
constexpr int SMEM_BYTES = SCHED + 4 * (kMaxRing + kTiles) - SB;
static_assert(SMEM_BYTES <= 232448, "smem");

constexpr int kLead = OPT_LEAD;

__host__ __device__ constexpr int tile_chunk0(int j) {
    return (j == 0 || j == 7) ? 4 : j == 1 ? 0 : j == 2 ? 2 : j == 3 ? 6 : j == 4 ? 8 : j == 5 ? 10 : 11;
}
__host__ __device__ constexpr int tile_nchunk(int j) { return j == 5 ? 1 : 2; }
__host__ __device__ constexpr int korder(int j, int kk) {
    constexpr int oa[13] = {11, 12, 0, 4, 1, 5, 2, 6, 3, 7, 8, 9, 10};
    if (j == 0) return oa[kk];
    if (OPT_KO && j >= 1 && j <= 4) return kk < OPT_KO ? kNSC + kk : kk < OPT_KO + kNSC ? kk - OPT_KO : kk;
    return kk;
}
__host__ __device__ constexpr int xload(int j, int kk) {
    constexpr int xa[13] = {-1, -1, -1, 4, -1, 5, 6, -1, 7, 8, -1, 9, 10};
    constexpr int xf[13] = {-1, -1, 4, 5, 6, 7, 8, 9, -1, 10, 11, -1, 12};
    return j == 0 ? xa[kk] : j == 7 ? xf[kk] : -1;
}
constexpr int kFirstS = 2;

enum { M_W64 = 0, M_W32, M_X0_R128, M_OUT_R128, M_X0_T2, M_X0_T1, M_OUT_T2, M_OUT_T1, M_WK0, M_WK1, M_WK2, M_COUNT };
struct Maps { CUtensorMap m[M_COUNT]; };

constexpr uint32_t E_HALF = 2u << 13, E_ISX = 1u << 19, E_EF = 1u << 20;
constexpr uint32_t T_ONE = 1u << 4, T_X0 = 1u << 5, T_BIAS = 1u << 6, T_STORE = 1u << 7, T_SREL = 1u << 11, T_XB = 1u << 14;
struct Sched { uint32_t e[kMaxRing + kTiles]; int n; };
constexpr uint32_t w_entry(int l, int k0, int atom, int kind) {
    return (uint32_t)((l * kD + k0) / 32) | (uint32_t)atom << 7 | (uint32_t)(kind == 2 ? M_W32 : M_W64) << 11 |
           (uint32_t)kind << 13;
}
constexpr Sched make_sched() {
    Sched s{};
    int n = 0;
    int start[kL * 7] = {};
    for (int c = 0; c < 13; ++c) {
        if (c >= kNSC) {
            if (n - OPT_PF0 - 3 >= kNS)
                for (int q = 1; q <= 4; ++q) s.e[n - OPT_PF0 - 4 + q] |= (uint32_t)q << 23 | (uint32_t)c << 27 | 1u << 31;
            s.e[n++] = (uint32_t)c << 7 | (uint32_t)M_X0_R128 << 11 | E_ISX;
        }
        s.e[n++] = w_entry(0, c * 64, tile_chunk0(3), 0);
        s.e[n++] = w_entry(0, c * 64, tile_chunk0(1), 0);
        s.e[n++] = w_entry(0, c * 64, tile_chunk0(2), 0);
    }
    for (int l = 0; l < kL; ++l) {
        for (int jj = 0; jj < 7; ++jj) {
            start[l * 7 + jj] = n;
            if (l == 0 && jj >= 1 && jj <= 3) continue;
            const int j = (l == 0 && jj == 0) ? 7 : jj;
            const int atom = tile_chunk0(j);
            const uint32_t wpf = (j == 4 && l < kL - 1) ? (uint32_t)(l + 1) : 0u;
            if (j == 5) {
                for (int kk = 0; kk < 13; kk += 2) s.e[n++] = w_entry(l, kk * 64, atom, kk < 12 ? 1 : 2);
                continue;
            }
            for (int kk = 0; kk < 13; ++kk) {
                const int c = korder(j, kk);
                const int xc = xload(j, kk);
                if (xc >= 0 && !(j == 6 && l == kL - 1)) {
                    uint32_t e = (uint32_t)xc << 7 | (uint32_t)(j == 7 ? M_X0_R128 : M_OUT_R128) << 11 | E_ISX;
                    if (j == 7) e |= E_EF;
                    else e |= (uint32_t)((xc - 4) / 2 + 1) << 15 | (uint32_t)((j == 6 ? l : l - 1) & 1) << 18;
                    s.e[n++] = e;
                }
                s.e[n++] = w_entry(l, c * 64, atom, 0) | (kk == 0 ? wpf << 21 : 0u);
            }
        }
    }
    s.n = n;
    int pos = n, tog = 0;
    for (int t = kL * 7 - 1; t >= 7; --t) {
        const int j = t % 7;
        if (pos > start[t] - OPT_PFD) pos = start[t] - OPT_PFD;
        const int nj = tile_nchunk(j) * 4;
        for (int q = nj; q >= 1; --q) {
            s.e[pos] |= (uint32_t)q << 23 | (uint32_t)tile_chunk0(j) << 27 | (tile_nchunk(j) == 1 ? 1u << 31 : 0u);
            pos -= (tog % 3 == 2) ? 1 : 2;
            ++tog;
        }
    }
    for (int t = 0; t < kTiles; ++t) {
        const int l = t / 7;
        const int l0order[7] = {3, 1, 2, 0, 4, 5, 6};
        const int j = l == 0 ? l0order[t] : t % 7;
        uint32_t e = (uint32_t)tile_chunk0(j) | (uint32_t)l << 12;
        if (j == 5) e |= T_ONE;
        if (l > 0 || t == 0) e |= T_X0;
        if (l > 0 || (t != 1 && t != 2)) e |= T_BIAS;
        if (t == 0) e |= T_XB;
        if (j != 6 || l == kL - 1) e |= T_STORE;
        if (l < kL - 1 && (j == 0 || (j >= 3 && j <= 5))) e |= (uint32_t)(j == 0 ? 1 : j - 1) << 8;
        if (j == 6 && l < kL - 1) e |= T_SREL;
        s.e[kMaxRing + t] = e;
    }
    return s;
}
constexpr Sched kSchedHost = make_sched();
constexpr int kRingLen = kSchedHost.n;
static_assert(kRingLen <= kMaxRing, "sched");
__device__ const Sched g_sched = make_sched();
static_assert((kSchedHost.e[0] | kSchedHost.e[1] | kSchedHost.e[2] | kSchedHost.e[3] | kSchedHost.e[4] | kSchedHost.e[5] |
               kSchedHost.e[6] | kSchedHost.e[7]) < (1u << 15), "the first ring entries are plain W slots");

__device__ __forceinline__ uint32_t smem_u32(const void* p) {
    return (uint32_t)__cvta_generic_to_shared(p);
}
__device__ __forceinline__ bool elect_one() {
    uint32_t p;
    asm volatile("{\n.reg .pred p;\nelect.sync _|p, 0xffffffff;\nselp.u32 %0, 1, 0, p;\n}" : "=r"(p));
    return p != 0;
}
__device__ __forceinline__ void mbar_init(uint32_t a, uint32_t cnt) {
    asm volatile("mbarrier.init.shared::cta.b64 [%0], %1;" ::"r"(a), "r"(cnt) : "memory");
}
__device__ __forceinline__ void mbar_expect_tx(uint32_t a, uint32_t bytes) {
    asm volatile("mbarrier.arrive.expect_tx.shared::cta.b64 _, [%0], %1;" ::"r"(a), "r"(bytes) : "memory");
}
__device__ __forceinline__ void mbar_arrive(uint32_t a) {
    asm volatile("mbarrier.arrive.shared::cta.b64 _, [%0];" ::"r"(a) : "memory");
}
__device__ __forceinline__ void mbar_wait(uint32_t a, uint32_t parity) {
    asm volatile(
        "{\n.reg .pred p, q;\n.reg .u32 n;\n"
        "mov.u32 n, 0;\n"
        "WAIT_%=:\n"
        "mbarrier.try_wait.parity.shared::cta.b64 p, [%0], %1;\n"
        "@p bra DONE_%=;\n"
        "add.u32 n, n, 1;\n"
        "setp.gt.u32 q, n, 16777216;\n"
        "@q trap;\n"
        "bra WAIT_%=;\n"
        "DONE_%=:\n}"
        ::"r"(a), "r"(parity) : "memory");
}
__device__ __forceinline__ void mbar_arrive_cluster(uint32_t a) {
    asm volatile("mbarrier.arrive.shared::cluster.b64 _, [%0];" ::"r"(a) : "memory");
}
__device__ __forceinline__ uint32_t mapa(uint32_t a, uint32_t rank) {
    uint32_t r;
    asm volatile("mapa.shared::cluster.u32 %0, %1, %2;" : "=r"(r) : "r"(a), "r"(rank));
    return r;
}
__device__ __forceinline__ void cluster_sync_all() {
    asm volatile("barrier.cluster.arrive.release.aligned;\nbarrier.cluster.wait.acquire.aligned;" ::: "memory");
}
__device__ __forceinline__ void tma_load_mc(uint32_t dst, const CUtensorMap* tm, int row, int atom, uint32_t bar) {
    asm volatile(
        "cp.async.bulk.tensor.3d.shared::cluster.global.mbarrier::complete_tx::bytes.multicast::cluster "
        "[%0], [%1, {%3, %4, %5}], [%2], %6;"
        ::"r"(dst), "l"(tm), "r"(bar), "r"(0), "r"(row), "r"(atom), "h"((uint16_t)3) : "memory");
}
__device__ __forceinline__ void tma_load_plain(uint32_t dst, const CUtensorMap* tm, int row, int atom, uint32_t bar) {
    asm volatile(
        "cp.async.bulk.tensor.3d.shared::cluster.global.mbarrier::complete_tx::bytes "
        "[%0], [%1, {%3, %4, %5}], [%2];"
        ::"r"(dst), "l"(tm), "r"(bar), "r"(0), "r"(row), "r"(atom) : "memory");
}
__device__ __forceinline__ void fence_proxy_async_smem() {
    asm volatile("fence.proxy.async.shared::cta;" ::: "memory");
}
__device__ __forceinline__ void fence_proxy_async_global() {
    asm volatile("fence.proxy.async.global;" ::: "memory");
}
__device__ __forceinline__ uint64_t policy_evict_first() {
    uint64_t p;
    asm volatile("createpolicy.fractional.L2::evict_first.b64 %0, 1.0;" : "=l"(p));
    return p;
}
__device__ __forceinline__ uint64_t policy_evict_normal() {
    uint64_t p;
    asm volatile("createpolicy.fractional.L2::evict_normal.b64 %0, 1.0;" : "=l"(p));
    return p;
}
__device__ __forceinline__ void tma_load(uint32_t dst, const CUtensorMap* tm, int row, int atom, uint32_t bar,
                                         uint64_t pol) {
    asm volatile(
        "cp.async.bulk.tensor.3d.shared::cluster.global.mbarrier::complete_tx::bytes.L2::cache_hint "
        "[%0], [%1, {%3, %4, %5}], [%2], %6;"
        ::"r"(dst), "l"(tm), "r"(bar), "r"(0), "r"(row), "r"(atom), "l"(pol) : "memory");
}
__device__ __forceinline__ void tma_store(const CUtensorMap* tm, int row, int atom, uint32_t src, uint64_t pol) {
    asm volatile("cp.async.bulk.tensor.3d.global.shared::cta.bulk_group.L2::cache_hint [%0, {%2, %3, %4}], [%1], %5;"
                 ::"l"(tm), "r"(src), "r"(0), "r"(row), "r"(atom), "l"(pol) : "memory");
}
__device__ __forceinline__ void bulk_load(uint32_t dst, const void* src, uint32_t bytes, uint32_t bar) {
    asm volatile(
        "cp.async.bulk.shared::cluster.global.mbarrier::complete_tx::bytes [%0], [%1], %2, [%3];"
        ::"r"(dst), "l"(src), "r"(bytes), "r"(bar) : "memory");
}
__device__ __forceinline__ void tma_prefetch(const CUtensorMap* tm, int row, int atom) {
    asm volatile("cp.async.bulk.prefetch.tensor.3d.L2.global [%0, {%1, %2, %3}];"
                 ::"l"(tm), "r"(0), "r"(row), "r"(atom) : "memory");
}
__device__ __forceinline__ void prefetch_l2(const void* p, uint32_t bytes) {
    asm volatile("cp.async.bulk.prefetch.L2.global [%0], %1;" ::"l"(p), "r"(bytes) : "memory");
}
__device__ __forceinline__ void bulk_commit() { asm volatile("cp.async.bulk.commit_group;" ::: "memory"); }
__device__ __forceinline__ void bulk_wait_read0() { asm volatile("cp.async.bulk.wait_group.read 0;" ::: "memory"); }
__device__ __forceinline__ void bulk_wait0() { asm volatile("cp.async.bulk.wait_group 0;" ::: "memory"); }
__device__ __forceinline__ void prefetch_tmap(const CUtensorMap* tm) {
    asm volatile("prefetch.tensormap [%0];" ::"l"(tm) : "memory");
}

__device__ __forceinline__ uint32_t pack_bf16(float lo, float hi) {
    uint32_t r;
    asm("cvt.rn.bf16x2.f32 %0, %1, %2;" : "=r"(r) : "f"(hi), "f"(lo));
    return r;
}
__device__ __forceinline__ uint32_t add_bf16x2(uint32_t a, uint32_t b) {
    uint32_t r;
    asm("add.rn.bf16x2 %0, %1, %2;" : "=r"(r) : "r"(a), "r"(b));
    return r;
}
__device__ __forceinline__ uint32_t fma_bf16x2(uint32_t a, uint32_t b, uint32_t c) {
    uint32_t r;
    asm("fma.rn.bf16x2 %0, %1, %2, %3;" : "=r"(r) : "r"(a), "r"(b), "r"(c));
    return r;
}

__device__ __forceinline__ void wgmma_fence() { asm volatile("wgmma.fence.sync.aligned;" ::: "memory"); }
__device__ __forceinline__ void wgmma_commit() { asm volatile("wgmma.commit_group.sync.aligned;" ::: "memory"); }
template <int N>
__device__ __forceinline__ void wgmma_wait() {
    asm volatile("wgmma.wait_group.sync.aligned %0;" ::"n"(N) : "memory");
}

#define ACC8(o) "+f"(d[o + 0]), "+f"(d[o + 1]), "+f"(d[o + 2]), "+f"(d[o + 3]), "+f"(d[o + 4]), "+f"(d[o + 5]), "+f"(d[o + 6]), "+f"(d[o + 7])
#define REGS32 "%0,%1,%2,%3,%4,%5,%6,%7,%8,%9,%10,%11,%12,%13,%14,%15,%16,%17,%18,%19,%20,%21,%22,%23,%24,%25,%26,%27,%28,%29,%30,%31"
#define REGS64 REGS32 ",%32,%33,%34,%35,%36,%37,%38,%39,%40,%41,%42,%43,%44,%45,%46,%47,%48,%49,%50,%51,%52,%53,%54,%55,%56,%57,%58,%59,%60,%61,%62,%63"

#define DESC_HI_STR "0x40000040"
constexpr uint32_t DESC_LO_B = (8192u >> 4) << 16;
constexpr uint32_t DESC_LO_A = 1u << 16;

template <int SCALE_D, uint32_t BOFF>
__device__ __forceinline__ void wgmma_rs_n128(float (&d)[64], uint32_t a0, uint32_t a1, uint32_t a2, uint32_t a3,
                                              uint32_t blo) {
    asm volatile(
        "{\n.reg .pred p;\n.reg .b32 lo;\n.reg .b64 db;\nsetp.ne.b32 p, %69, 0;\n"
        "add.u32 lo, %68, %70;\nmov.b64 db, {lo, " DESC_HI_STR "};\n"
        "wgmma.mma_async.sync.aligned.m64n128k16.f32.bf16.bf16 {" REGS64 "}, {%64,%65,%66,%67}, db, p, 1, 1, 1;\n}"
        : ACC8(0), ACC8(8), ACC8(16), ACC8(24), ACC8(32), ACC8(40), ACC8(48), ACC8(56)
        : "r"(a0), "r"(a1), "r"(a2), "r"(a3), "r"(blo), "n"(SCALE_D), "n"(BOFF));
}
template <int SCALE_D, uint32_t AOFF, uint32_t BOFF>
__device__ __forceinline__ void wgmma_ss_n128(float (&d)[64], uint32_t alo, uint32_t blo) {
    asm volatile(
        "{\n.reg .pred p;\n.reg .b32 lo, lo2;\n.reg .b64 da, db;\nsetp.ne.b32 p, %66, 0;\n"
        "add.u32 lo, %64, %67;\nmov.b64 da, {lo, " DESC_HI_STR "};\n"
        "add.u32 lo2, %65, %68;\nmov.b64 db, {lo2, " DESC_HI_STR "};\n"
        "wgmma.mma_async.sync.aligned.m64n128k16.f32.bf16.bf16 {" REGS64 "}, da, db, p, 1, 1, 0, 1;\n}"
        : ACC8(0), ACC8(8), ACC8(16), ACC8(24), ACC8(32), ACC8(40), ACC8(48), ACC8(56)
        : "r"(alo), "r"(blo), "n"(SCALE_D), "n"(AOFF), "n"(BOFF));
}
template <int SCALE_D, uint32_t BOFF>
__device__ __forceinline__ void wgmma_rs_n64(float (&d)[64], uint32_t a0, uint32_t a1, uint32_t a2, uint32_t a3,
                                             uint32_t blo) {
    asm volatile(
        "{\n.reg .pred p;\n.reg .b32 lo;\n.reg .b64 db;\nsetp.ne.b32 p, %37, 0;\n"
        "add.u32 lo, %36, %38;\nmov.b64 db, {lo, " DESC_HI_STR "};\n"
        "wgmma.mma_async.sync.aligned.m64n64k16.f32.bf16.bf16 {" REGS32 "}, {%32,%33,%34,%35}, db, p, 1, 1, 1;\n}"
        : ACC8(0), ACC8(8), ACC8(16), ACC8(24)
        : "r"(a0), "r"(a1), "r"(a2), "r"(a3), "r"(blo), "n"(SCALE_D), "n"(BOFF));
}
template <int SCALE_D, uint32_t AOFF, uint32_t BOFF>
__device__ __forceinline__ void wgmma_ss_n64(float (&d)[64], uint32_t alo, uint32_t blo) {
    asm volatile(
        "{\n.reg .pred p;\n.reg .b32 lo, lo2;\n.reg .b64 da, db;\nsetp.ne.b32 p, %34, 0;\n"
        "add.u32 lo, %32, %35;\nmov.b64 da, {lo, " DESC_HI_STR "};\n"
        "add.u32 lo2, %33, %36;\nmov.b64 db, {lo2, " DESC_HI_STR "};\n"
        "wgmma.mma_async.sync.aligned.m64n64k16.f32.bf16.bf16 {" REGS32 "}, da, db, p, 1, 1, 0, 1;\n}"
        : ACC8(0), ACC8(8), ACC8(16), ACC8(24)
        : "r"(alo), "r"(blo), "n"(SCALE_D), "n"(AOFF), "n"(BOFF));
}
template <int T, uint32_t OFF>
__device__ __forceinline__ void ldsm4x(uint32_t base, uint32_t& r0, uint32_t& r1, uint32_t& r2, uint32_t& r3) {
    asm volatile("{\n.reg .b32 ad;\nxor.b32 ad, %4, %5;\n"
                 "ldmatrix.sync.aligned.m8n8.x4.shared.b16 {%0,%1,%2,%3}, [ad + %6];\n}"
                 : "=r"(r0), "=r"(r1), "=r"(r2), "=r"(r3) : "r"(base), "n"(T * 32), "n"(OFF) : "memory");
}
template <int T, uint32_t OFF>
__device__ __forceinline__ void stsm4x(uint32_t base, uint32_t r0, uint32_t r1, uint32_t r2, uint32_t r3) {
    asm volatile("{\n.reg .b32 ad;\nxor.b32 ad, %0, %5;\n"
                 "stmatrix.sync.aligned.m8n8.x4.shared.b16 [ad + %6], {%1,%2,%3,%4};\n}"
                 ::"r"(base), "r"(r0), "r"(r1), "r"(r2), "r"(r3), "n"(T * 32), "n"(OFF) : "memory");
}
template <uint32_t OFF>
__device__ __forceinline__ void ldsm16(uint32_t base, uint32_t* r) {
    ldsm4x<0, OFF>(base, r[0], r[1], r[2], r[3]);
    ldsm4x<1, OFF>(base, r[4], r[5], r[6], r[7]);
    ldsm4x<2, OFF>(base, r[8], r[9], r[10], r[11]);
    ldsm4x<3, OFF>(base, r[12], r[13], r[14], r[15]);
}
template <uint32_t OFF>
__device__ __forceinline__ void stsm16(uint32_t base, const uint32_t* r) {
    stsm4x<0, OFF>(base, r[0], r[1], r[2], r[3]);
    stsm4x<1, OFF>(base, r[4], r[5], r[6], r[7]);
    stsm4x<2, OFF>(base, r[8], r[9], r[10], r[11]);
    stsm4x<3, OFF>(base, r[12], r[13], r[14], r[15]);
}
template <uint32_t OFF>
__device__ __forceinline__ uint32_t lds32x(uint32_t base) {
    uint32_t v;
    asm volatile("ld.shared.b32 %0, [%1 + %2];" : "=r"(v) : "r"(base), "n"(OFF) : "memory");
    return v;
}

#define PROF_ST(idx)
#define PROF_MARK(idx)
#define PROF_GT(idx)

struct Ctx {
    uint32_t it;
    uint32_t tb;
    uint32_t wg;
    uint32_t tcnt;
    uint32_t bb;
    uint32_t sr;
    uint32_t rel;
    bool lane0, lane01;
};

__device__ __forceinline__ void release_slot(const Ctx& c, uint32_t slot) {
    if (c.lane0) mbar_arrive(BAR_EMPTY + slot * 8);
}
__device__ __forceinline__ uint32_t wait_slot(Ctx& cx) {
    const uint32_t slot = cx.it & (kNS - 1);
    mbar_wait(cx.sr + BAR_FULL + slot * 8, (cx.it / kNS) & 1);
    cx.it++;
    return slot;
}
__device__ __forceinline__ void publish_stage(Ctx& cx) {
    fence_proxy_async_smem();
    __syncwarp();
    if (cx.lane0) mbar_arrive(cx.sr + BAR_OUTRDY + cx.wg * 8);
    PROF_MARK(3);
    cx.tcnt++;
}

template <uint32_t OFF>
__device__ __forceinline__ void ld_bias(const Ctx& cx, uint32_t* b) {
    ldsm4x<0, BIAS + OFF>(cx.bb, b[0], b[1], b[2], b[3]);
    ldsm4x<0, BIAS + OFF + 64>(cx.bb, b[4], b[5], b[6], b[7]);
}
template <int H>
__device__ __forceinline__ void pack_bias(const float (&acc)[64], const uint32_t* b, uint32_t* p) {
#pragma unroll
    for (int i = 0; i < 16; ++i)
        p[i] = add_bf16x2(pack_bf16(acc[32 * H + 2 * i], acc[32 * H + 2 * i + 1]), b[i >> 1]);
}
template <uint32_t BOFF, uint32_t XOFF>
__device__ __forceinline__ void epi_self(Ctx& cx, const float (&acc)[64]) {
    uint32_t b[16], p[32], x[32];
    ld_bias<BOFF>(cx, b);
    ld_bias<BOFF + 128>(cx, b + 8);
    pack_bias<0>(acc, b, p);
    ldsm16<XOFF>(cx.tb, x);
    pack_bias<1>(acc, b + 8, p + 16);
    ldsm16<XOFF + 8192>(cx.tb, x + 16);
#pragma unroll
    for (int i = 0; i < 32; ++i) x[i] = fma_bf16x2(x[i], p[i], x[i]);
    if constexpr (XOFF != STG) {
        PROF_MARK(0);
        PROF_GT(1);
        mbar_wait(cx.sr + BAR_STGFULL + cx.wg * 8, cx.tcnt & 1);
        PROF_MARK(2);
    }
    stsm16<STG>(cx.tb, x);
    stsm16<STG + 8192>(cx.tb, x + 16);
    publish_stage(cx);
}

template <bool N64, bool FIRST, int C, uint32_t BOFF>
__device__ __forceinline__ void mma_chunk(const Ctx& cx, uint32_t (&a)[kNRC][16], float (&acc)[64], const uint32_t blo) {
    constexpr int F = FIRST ? 0 : 1;
    if constexpr (C < kNSC) {
        const uint32_t alo = cx.wg * (kWgStride >> 4);
        constexpr uint32_t A0 = DESC_LO_A + ((SREG + C * 8192) >> 4);
        if constexpr (N64) {
            wgmma_ss_n64<F, A0, BOFF>(acc, alo, blo);
            wgmma_ss_n64<1, A0 + 2, BOFF + 128>(acc, alo, blo);
            wgmma_ss_n64<1, A0 + 4, BOFF + 256>(acc, alo, blo);
            wgmma_ss_n64<1, A0 + 6, BOFF + 384>(acc, alo, blo);
        } else {
            wgmma_ss_n128<F, A0, BOFF>(acc, alo, blo);
            wgmma_ss_n128<1, A0 + 2, BOFF + 128>(acc, alo, blo);
            wgmma_ss_n128<1, A0 + 4, BOFF + 256>(acc, alo, blo);
            wgmma_ss_n128<1, A0 + 6, BOFF + 384>(acc, alo, blo);
        }
    } else {
        uint32_t(&r)[16] = a[C - kNSC];
        if constexpr (N64) {
            wgmma_rs_n64<F, BOFF>(acc, r[0], r[1], r[2], r[3], blo);
            wgmma_rs_n64<1, BOFF + 128>(acc, r[4], r[5], r[6], r[7], blo);
            wgmma_rs_n64<1, BOFF + 256>(acc, r[8], r[9], r[10], r[11], blo);
            wgmma_rs_n64<1, BOFF + 384>(acc, r[12], r[13], r[14], r[15], blo);
        } else {
            wgmma_rs_n128<F, BOFF>(acc, r[0], r[1], r[2], r[3], blo);
            wgmma_rs_n128<1, BOFF + 128>(acc, r[4], r[5], r[6], r[7], blo);
            wgmma_rs_n128<1, BOFF + 256>(acc, r[8], r[9], r[10], r[11], blo);
            wgmma_rs_n128<1, BOFF + 384>(acc, r[12], r[13], r[14], r[15], blo);
        }
    }
}

constexpr uint32_t B0 = DESC_LO_B + (RING >> 4);

template <int J, int KK>
__device__ __forceinline__ void k_step(Ctx& cx, uint32_t (&a)[kNRC][16], float (&acc)[64], const int l, uint32_t& prev,
                                       const float (&accB)[64], const float (&accC)[64]) {
    constexpr bool kN64 = (tile_nchunk(J) == 1);
    constexpr int kSteps = kN64 ? 7 : 13;
    if constexpr (KK < kSteps) {
        constexpr int C = kN64 ? 2 * KK : korder(J, KK);
        if constexpr (KK == 0 && J != 7) {
            if (cx.wg == 1) {
                publish_stage(cx);
                PROF_MARK(0);
                PROF_GT(1);
                asm volatile("bar.sync 1, 256;" ::: "memory");
            }
        }
        constexpr int XC = kN64 ? -1 : xload(J, KK);
        if constexpr (XC >= 0) {
            const uint32_t slot = wait_slot(cx);
            ldsm16<RING>(cx.tb + slot * kSlot - cx.wg * (kWgStride - 8192), a[XC - kNSC]);
            __syncwarp();
            release_slot(cx, slot);
        }
        if constexpr (J == 0 && KK == kFirstS) mbar_wait(cx.sr + BAR_SFULL + cx.wg * 8, (l - 1) & 1);
        const uint32_t slot = wait_slot(cx);
        const uint32_t blo = slot * (kSlot >> 4);
        wgmma_fence();
        mma_chunk<kN64, KK == 0, C, B0>(cx, a, acc, blo);
        if constexpr (kN64 && C + 1 < 13) mma_chunk<kN64, false, C + 1, B0 + (8192 >> 4)>(cx, a, acc, blo);
        wgmma_commit();
        if constexpr (KK == 0 && J != 7) {
            if (cx.wg == 0) {
                publish_stage(cx);
                PROF_MARK(0);
                PROF_GT(1);
            }
        }
        if constexpr (J != 7 && KK == kLead + ((J == 1 || J == 2) ? OPT_LEADS : 0)) {
            if (cx.wg == 0) asm volatile("bar.arrive 1, 256;" ::: "memory");
        }
        if constexpr (J == 7 && KK <= 3) {
            if constexpr (KK == 1) epi_self<256, SREG>(cx, accB);
            if constexpr (KK == 3) epi_self<512, SREG + 2 * 8192>(cx, accC);
            if constexpr (KK == 2) {
                wgmma_wait<1>();
                release_slot(cx, (prev - 1) & (kNS - 1));
                release_slot(cx, prev);
            }
            if constexpr (KK == 3) {
                wgmma_wait<1>();
                release_slot(cx, prev);
            }
        } else if constexpr (KK > 0) {
            wgmma_wait<1>();
            if (J != 6 || KK - 1 < 13 - kNS || l != kL - 1) release_slot(cx, prev);
            if constexpr (J == 6 && KK == kNSC) {
                if (cx.lane0) mbar_arrive(cx.sr + BAR_SFREE + cx.wg * 8);
            }
        }
        prev = slot;
        k_step<J, KK + 1>(cx, a, acc, l, prev, accB, accC);
    }
}

template <int J>
__device__ __forceinline__ void epi_tile(const Ctx& cx, uint32_t (&a)[kNRC][16], const float (&acc)[64],
                                         const uint32_t* b, const int l) {
    constexpr int C = tile_chunk0(J);
    constexpr int NH = tile_nchunk(J);
    uint32_t p[32];
    if constexpr (C < kNSC) {
        uint32_t xl[16], x0[16];
        pack_bias<0>(acc, b, p);
        pack_bias<1>(acc, b + 8, p + 16);
        asm volatile("" ::"r"(p[0]), "r"(p[2]), "r"(p[4]), "r"(p[6]), "r"(p[8]), "r"(p[10]), "r"(p[12]), "r"(p[14]),
                     "r"(p[17]), "r"(p[19]), "r"(p[21]), "r"(p[23]), "r"(p[25]), "r"(p[27]), "r"(p[29]), "r"(p[31]) : "memory");
        __syncwarp();
        ldsm16<SREG + C * 8192>(cx.tb, xl);
        ldsm16<STG>(cx.tb, x0);
#pragma unroll
        for (int i = 0; i < 16; ++i) xl[i] = fma_bf16x2(x0[i], p[i], xl[i]);
        stsm16<STG>(cx.tb, xl);
        __syncwarp();
        ldsm16<SREG + (C + 1) * 8192>(cx.tb, xl);
        ldsm16<STG + 8192>(cx.tb, x0);
#pragma unroll
        for (int i = 0; i < 16; ++i) xl[i] = fma_bf16x2(x0[i], p[16 + i], xl[i]);
        stsm16<STG + 8192>(cx.tb, xl);
    } else {
        uint32_t o[32];
        if (J <= 3 || (J != 7 && l != 0)) {
            pack_bias<0>(acc, b, p);
            ldsm16<STG>(cx.tb, o);
            if constexpr (NH == 2) {
                pack_bias<1>(acc, b + 8, p + 16);
                ldsm16<STG + 8192>(cx.tb, o + 16);
            }
#pragma unroll
            for (int i = 0; i < 16 * NH; ++i) o[i] = fma_bf16x2(o[i], p[i], a[C - kNSC + i / 16][i % 16]);
        } else {
            pack_bias<0>(acc, b, p);
            if constexpr (NH == 2) pack_bias<1>(acc, b + 8, p + 16);
#pragma unroll
            for (int i = 0; i < 16 * NH; ++i)
                o[i] = fma_bf16x2(a[C - kNSC + i / 16][i % 16], p[i], a[C - kNSC + i / 16][i % 16]);
        }
        if constexpr (J == 6) {
#pragma unroll
            for (int i = 0; i < 32; ++i) a[C - kNSC + i / 16][i % 16] = o[i];
        }
        if (J != 6 || l == kL - 1) {
            stsm16<STG>(cx.tb, o);
            if constexpr (NH == 2) stsm16<STG + 8192>(cx.tb, o + 16);
        }
    }
}

template <int J>
__device__ __forceinline__ void do_tile(Ctx& cx, uint32_t (&a)[kNRC][16], float (&acc)[64], const int l,
                                        const float (&accB)[64], const float (&accC)[64]) {
    uint32_t prev = 0;
    k_step<J, 0>(cx, a, acc, l, prev, accB, accC);
    mbar_wait(cx.sr + BAR_STGFULL + cx.wg * 8, cx.tcnt & 1);
    uint32_t b[16];
    ld_bias<0>(cx, b);
    if constexpr (tile_nchunk(J) == 2) ld_bias<128>(cx, b + 8);
    wgmma_wait<0>();
    if (J != 6 || l != kL - 1) release_slot(cx, prev);
    if constexpr (J == 7) {
        PROF_MARK(0);
        PROF_GT(1);
    }
    PROF_MARK(2);
    epi_tile<J>(cx, a, acc, b, l);
}

__device__ __forceinline__ void ss_group(Ctx& cx, float (&acc)[64], const uint32_t alo, uint32_t& prev, const bool rel) {
    const uint32_t slot = wait_slot(cx);
    const uint32_t blo = slot * (kSlot >> 4);
    wgmma_fence();
    wgmma_ss_n128<1, DESC_LO_A, B0>(acc, alo, blo);
    wgmma_ss_n128<1, DESC_LO_A + 2, B0 + 128>(acc, alo, blo);
    wgmma_ss_n128<1, DESC_LO_A + 4, B0 + 256>(acc, alo, blo);
    wgmma_ss_n128<1, DESC_LO_A + 6, B0 + 384>(acc, alo, blo);
    wgmma_commit();
    wgmma_wait<1>();
    if (rel) release_slot(cx, prev);
    prev = slot;
}

__device__ __forceinline__ void fused_pass(Ctx& cx, float (&accD)[64], float (&accB)[64], float (&accC)[64]) {
#pragma unroll
    for (int i = 0; i < 64; ++i) { accD[i] = 0.f; accB[i] = 0.f; accC[i] = 0.f; }
    PROF_MARK(0);
    PROF_GT(1);
    uint32_t prev = 0, xslot = 0;
#pragma unroll 1
    for (int c = 0; c < 13; ++c) {
        uint32_t alo;
        const uint32_t xprev = xslot;
        if (c < kNSC) {
            mbar_wait(cx.sr + BAR_SFULLC + c * 8, 0);
            alo = (SREG + c * 8192 + cx.wg * kWgStride) >> 4;
        } else {
            xslot = wait_slot(cx);
            alo = (RING + xslot * kSlot + cx.wg * 8192) >> 4;
        }
        ss_group(cx, accD, alo, prev, c > 0);
        if (c > kNSC) release_slot(cx, xprev);
        if (c == OPT_FS && cx.wg == 1) asm volatile("bar.sync 1, 256;" ::: "memory");
        ss_group(cx, accB, alo, prev, true);
        if (c == OPT_FS + 1 && cx.wg == 0) asm volatile("bar.arrive 1, 256;" ::: "memory");
        ss_group(cx, accC, alo, prev, true);
    }
    mbar_wait(cx.sr + BAR_STGFULL + cx.wg * 8, 0);
    PROF_MARK(2);
    epi_self<0, STG>(cx, accD);
    wgmma_wait<0>();
    release_slot(cx, prev);
    release_slot(cx, xslot);
}

__device__ __forceinline__ void load_s_chunk(const Maps& maps, uint32_t sr, int row0, int c, uint64_t pol) {
    const uint32_t bar = sr + BAR_SFULLC + c * 8;
    mbar_expect_tx(bar, 16384);
    tma_load(sr + SREG + c * 8192, &maps.m[M_X0_T1], row0, c, bar, pol);
    tma_load(sr + SREG + kWgStride + c * 8192, &maps.m[M_X0_T1], row0 + 64, c, bar, pol);
}

__global__ void
__launch_bounds__(384, 1)
dcn_kernel(const __grid_constant__ Maps maps, const __nv_bfloat16* __restrict__ bs,
           const __nv_bfloat16* __restrict__ ws, const __nv_bfloat16* __restrict__ x0) {
    extern __shared__ uint8_t smem_raw[];
    if (smem_u32(smem_raw) != SB) __trap();
    constexpr uint32_t sr = 0, rank = 0;
    const int warp = __shfl_sync(0xffffffffu, threadIdx.x >> 5, 0);
    const int lane = threadIdx.x & 31;
    const int row0 = blockIdx.x * kBM;
    constexpr uint32_t kWShare = kD * kD * 2 / 128;

    if (threadIdx.x == 288) {
        for (int j = 0; j < kNSC; ++j) mbar_init(sr + BAR_SFULLC + j * 8, 1);
        asm volatile("fence.mbarrier_init.release.cluster;" ::: "memory");
        fence_proxy_async_smem();
        const uint64_t pol_x = policy_evict_first();
        PROF_ST(0);
        for (int c = 0; c < 2; ++c) load_s_chunk(maps, sr, row0, c, pol_x);
        PROF_ST(1);
    }
    if (threadIdx.x == 0) {
        for (int s = 0; s < kNS; ++s) {
            mbar_init(sr + BAR_FULL + s * 8, 1);
            mbar_init(sr + BAR_EMPTY + s * 8, OPT_MC ? 16 : 8);
        }
        for (int w = 0; w < 2; ++w) {
            mbar_init(sr + BAR_SFULL + w * 8, 1);
            mbar_init(sr + BAR_SFREE + w * 8, 4);
            mbar_init(sr + BAR_STGFULL + w * 8, 1);
            mbar_init(sr + BAR_OUTRDY + w * 8, 4);
        }
        for (int j = 0; j < 4; ++j) mbar_init(sr + BAR_XREADY + j * 8, 2);
        asm volatile("fence.mbarrier_init.release.cluster;" ::: "memory");
    }
    if (warp == 8 && lane < M_COUNT) prefetch_tmap(&maps.m[lane]);
    uint32_t se0 = 0, se1 = 0;
    if (warp < 8) {
        se0 = __ldg(&g_sched.e[threadIdx.x]);
        if (threadIdx.x + 256 < kMaxRing + kTiles) se1 = __ldg(&g_sched.e[threadIdx.x + 256]);
    }
    if (threadIdx.x == 0) PROF_ST(2);
    if (threadIdx.x == 32) PROF_ST(3);
    __syncthreads();
    if (threadIdx.x == 0) PROF_ST(4);
    if (threadIdx.x == 0) PROF_ST(5);

    if (warp >= 8) {
        asm volatile("setmaxnreg.dec.sync.aligned.u32 24;");
        if (warp == 8 || warp == 11) {
            const uint64_t pol_x = policy_evict_first();
            const uint64_t pol_n = policy_evict_normal();
#pragma unroll 1
            for (uint32_t it = (warp == 8 ? 0 : 1); it < (uint32_t)kRingLen; it += 2) {
                uint32_t e;
                if (it < kNS) {
                    const uint32_t c = it / 3, j = it - 3 * c;
                    e = 2 * c + (((j == 0 ? 6u : 2u * j - 2u) + rank) << 7);
                } else {
                    if (it < kNS + 2) asm volatile("bar.sync 2, 384;" ::: "memory");
                    e = lds32x<SCHED>(sr + it * 4);
                }
                const uint32_t slot = it & (kNS - 1);
                const uint32_t xw = (e >> 15) & 7;
                if (xw) mbar_wait(sr + BAR_XREADY - 8 + xw * 8, (e >> 18) & 1);
                mbar_wait(sr + BAR_EMPTY + slot * 8, ((it / kNS) & 1) ^ 1);
                if (elect_one()) {
                    const uint32_t fb = sr + BAR_FULL + slot * 8;
                    mbar_expect_tx(fb, (e & E_HALF) ? 8192 : 16384);
                    const CUtensorMap* tm = &maps.m[(e >> 11) & 3];
                    if (e & E_ISX)
                        tma_load(sr + RING + slot * kSlot, tm, row0, (e >> 7) & 15, fb, (e & E_EF) ? pol_x : pol_n);
                    else
                        tma_load_plain(RING + slot * kSlot, &maps.m[M_WK0 + ((e >> 13) & 3)], (int)(e & 127) * 32,
                                       (e >> 7) & 15, fb);
                    const uint32_t wpf = (e >> 21) & 3;
                    if (wpf) prefetch_l2((const char*)ws + (size_t)wpf * (kD * kD * 2) + blockIdx.x * kWShare, kWShare);
                }
                __syncwarp();
                const uint32_t job = (e >> 23) & 15;
                if (job) {
                    const uint32_t one = e >> 31;
                    const uint32_t r = one ? (job - 1) * 32 + lane : (job - 1) * 16 + (lane >> 1);
                    const uint32_t at = ((e >> 27) & 15) + (one ? 0 : (lane & 1));
                    const char* pa = (const char*)x0 + (uint32_t)((row0 + r) * (kD * 2) + at * 128);
                    asm volatile("prefetch.global.L2 [%0];" ::"l"(pa));
                }
            }
        } else {
            if (warp == 9 && lane == 0) {
                const uint64_t pol_x = policy_evict_first();
                for (int c = 2; c < kNSC; ++c) {
                    mbar_wait(sr + BAR_SFULLC + (c - 2) * 8, 0);
                    PROF_ST(4 + c);
                    if (c == 2) prefetch_l2((const char*)ws + blockIdx.x * kWShare, kWShare);
                    load_s_chunk(maps, sr, row0, c, pol_x);
                }
            }
            __syncwarp();
            asm volatile("bar.sync 2, 384;" ::: "memory");
            if (lane == 0) {
                const int w = warp - 9;
                const int rw = row0 + w * 64;
                const uint32_t stg = sr + STG + w * kWgStride;
                const uint32_t sreg = sr + SREG + w * kWgStride;
                const uint32_t stgfull = sr + BAR_STGFULL + w * 8;
                const uint64_t pol_x = policy_evict_first();
                const uint64_t pol_n = policy_evict_normal();
                mbar_wait(sr + BAR_SFULLC + (kNSC - 1) * 8, 0);
                if (w == 0) PROF_ST(8);
                uint32_t pub = 0;
#pragma unroll 1
                for (uint32_t t = 0; t < (uint32_t)kTiles; ++t) {
                    const uint32_t e = lds32x<SCHED + 4 * kMaxRing>(sr + t * 4);
                    const uint32_t c0 = e & 15, one = (e >> 4) & 1, l = (e >> 12) & 3;
                    mbar_expect_tx(stgfull, ((e & T_BIAS) ? (256u >> one) : 0u) + ((e & T_X0) ? (16384u >> one) : 0u) +
                                                ((e & T_XB) ? 512u : 0u));
                    if (e & T_BIAS) bulk_load(sr + BIAS + w * kBiasStride, bs + l * kD + c0 * 64, 256u >> one, stgfull);
                    if (e & T_XB) bulk_load(sr + BIAS + w * kBiasStride + 256, bs, 512, stgfull);
                    if (e & T_X0) tma_load(stg, &maps.m[M_X0_T2 + one], rw, c0, stgfull, t == 0 ? pol_n : pol_x);
                    bulk_wait0();
                    if (pub) {
                        fence_proxy_async_global();
                        mbar_arrive(sr + BAR_XREADY - 8 + pub * 8);
                    }
                    pub = (e >> 8) & 7;
                    if (e & T_SREL) {
                        const uint32_t sfull = sr + BAR_SFULL + w * 8;
                        mbar_wait(sr + BAR_SFREE + w * 8, l & 1);
                        mbar_expect_tx(sfull, kNSC * 8192);
#pragma unroll 1
                        for (int c = 0; c < kNSC; ++c) {
                            tma_load(sreg + c * 8192, &maps.m[M_OUT_T1], rw, c, sfull, pol_n);
                            if (c < kNSC - 1) __nanosleep(OPT_SNS);
                        }
                    }
                    mbar_wait(sr + BAR_OUTRDY + w * 8, t & 1);
                    if (e & T_STORE) {
                        tma_store(&maps.m[M_OUT_T2 + one], rw, c0, stg, l == kL - 1 ? pol_x : pol_n);
                        bulk_commit();
                        bulk_wait_read0();
                    }
                }
            }
        }
    } else {
        asm volatile("setmaxnreg.inc.sync.aligned.u32 240;");
        {
            if (!(se0 & E_ISX)) se0 += rank * (((se0 >> 13) & 3) == 0 ? (1u << 7) : ((se0 >> 13) & 3) == 1 ? 2u : 1u);
            if (threadIdx.x + 256 < kMaxRing && !(se1 & E_ISX))
                se1 += rank * (((se1 >> 13) & 3) == 0 ? (1u << 7) : ((se1 >> 13) & 3) == 1 ? 2u : 1u);
            asm volatile("st.shared.b32 [%0], %1;" ::"r"(sr + SCHED + threadIdx.x * 4), "r"(se0) : "memory");
            if (threadIdx.x + 256 < kMaxRing + kTiles)
                asm volatile("st.shared.b32 [%0], %1;" ::"r"(sr + SCHED + threadIdx.x * 4 + 1024), "r"(se1) : "memory");
            asm volatile("bar.arrive 2, 384;" ::: "memory");
        }
        Ctx cx;
        cx.it = 0;
        cx.wg = warp >> 2;
        cx.lane0 = (lane == 0);
        cx.tcnt = 0;
        {
            const int r = (warp & 3) * 16 + (lane & 7) + ((lane >> 3) & 1) * 8;
            cx.tb = sr + r * 128 + (((lane >> 4) ^ (lane & 7)) * 16) + cx.wg * kWgStride;
            cx.bb = sr + (lane >> 3) * 16 + cx.wg * kBiasStride;
            cx.sr = sr;
            cx.lane01 = lane < 2;
        }
        uint32_t a[kNRC][16];
        float acc[64];
        {
            float accB[64], accC[64];
            fused_pass(cx, acc, accB, accC);
            do_tile<7>(cx, a, acc, 0, accB, accC);
        }
        int l = 0;
#pragma unroll 1
        while (true) {
            do_tile<4>(cx, a, acc, l, acc, acc);
            do_tile<5>(cx, a, acc, l, acc, acc);
            do_tile<6>(cx, a, acc, l, acc, acc);
            if (++l == kL) break;
            do_tile<0>(cx, a, acc, l, acc, acc);
            do_tile<1>(cx, a, acc, l, acc, acc);
            do_tile<2>(cx, a, acc, l, acc, acc);
            do_tile<3>(cx, a, acc, l, acc, acc);
        }
        publish_stage(cx);
    }
}

typedef CUresult (*EncodeFn)(CUtensorMap*, CUtensorMapDataType, cuuint32_t, void*, const cuuint64_t*,
                             const cuuint64_t*, const cuuint32_t*, const cuuint32_t*, CUtensorMapInterleave,
                             CUtensorMapSwizzle, CUtensorMapL2promotion, CUtensorMapFloatOOBfill);

bool encode3d(EncodeFn fn, CUtensorMap* tm, const void* ptr, uint64_t rows, uint32_t brows, uint32_t batoms) {
    cuuint64_t dims[3] = {64, rows, 13};
    cuuint64_t strides[2] = {kD * 2, 128};
    cuuint32_t box[3] = {64, brows, batoms};
    cuuint32_t es[3] = {1, 1, 1};
    return fn(tm, CU_TENSOR_MAP_DATA_TYPE_BFLOAT16, 3, const_cast<void*>(ptr), dims, strides, box, es,
              CU_TENSOR_MAP_INTERLEAVE_NONE, CU_TENSOR_MAP_SWIZZLE_128B, CU_TENSOR_MAP_L2_PROMOTION_L2_256B,
              CU_TENSOR_MAP_FLOAT_OOB_FILL_NONE) == CUDA_SUCCESS;
}

}

extern "C" void kernel_launch(void* const* d_in, const int* in_sizes, int n_in, void* d_out, int out_size) {
    (void)in_sizes; (void)n_in; (void)out_size;
    static EncodeFn fn = nullptr;
    if (!fn) {
        void* p = nullptr;
        cudaDriverEntryPointQueryResult qr;
        cudaGetDriverEntryPoint("cuTensorMapEncodeTiled", &p, cudaEnableDefault, &qr);
        fn = (EncodeFn)p;
        cudaFuncSetAttribute(dcn_kernel, cudaFuncAttributeMaxDynamicSharedMemorySize, SMEM_BYTES);
    }
    if (!fn) return;
    Maps maps;
    encode3d(fn, &maps.m[M_W64], d_in[1], (uint64_t)kL * kD, 64, 1);
    encode3d(fn, &maps.m[M_W32], d_in[1], (uint64_t)kL * kD, 32, 1);
    encode3d(fn, &maps.m[M_WK0], d_in[1], (uint64_t)kL * kD, 64, 2);
    encode3d(fn, &maps.m[M_WK1], d_in[1], (uint64_t)kL * kD, 128, 1);
    encode3d(fn, &maps.m[M_WK2], d_in[1], (uint64_t)kL * kD, 64, 1);
    encode3d(fn, &maps.m[M_X0_R128], d_in[0], kB, 128, 1);
    encode3d(fn, &maps.m[M_OUT_R128], d_out, kB, 128, 1);
    encode3d(fn, &maps.m[M_X0_T2], d_in[0], kB, 64, 2);
    encode3d(fn, &maps.m[M_X0_T1], d_in[0], kB, 64, 1);
    encode3d(fn, &maps.m[M_OUT_T2], d_out, kB, 64, 2);
    encode3d(fn, &maps.m[M_OUT_T1], d_out, kB, 64, 1);
    dcn_kernel<<<kB / kBM, 384, SMEM_BYTES>>>(maps, (const __nv_bfloat16*)d_in[2], (const __nv_bfloat16*)d_in[1],
                                              (const __nv_bfloat16*)d_in[0]);
}
```

```cpp
#include <cuda_runtime.h>
#include <cuda_bf16.h>
#include <cuda.h>
#include <stdint.h>

namespace {

constexpr int kB = 16384;
constexpr int kD = 832;
constexpr int kL = 3;
constexpr int kBM = 128;
constexpr int kNS = 8;
constexpr int kSlot = 16384;
constexpr int kNSC = 4;
constexpr int kNRC = 9;

constexpr uint32_t SB = 1024;
constexpr uint32_t RING = SB;
constexpr uint32_t WGB = RING + kNS * kSlot;
constexpr uint32_t kWgStride = (kNSC + 2) * 8192;
constexpr uint32_t SREG = WGB;
constexpr uint32_t STG = WGB + kNSC * 8192;
constexpr uint32_t BIAS = WGB + 2 * kWgStride;
constexpr uint32_t kBiasStride = 768;
constexpr uint32_t BAR_FULL = BIAS + 2 * kBiasStride;
constexpr uint32_t BAR_EMPTY = BAR_FULL + 8 * kNS;
constexpr uint32_t BAR_SFULL = BAR_EMPTY + 8 * kNS;
constexpr uint32_t BAR_SFREE = BAR_SFULL + 16;
constexpr uint32_t BAR_STGFULL = BAR_SFREE + 16;
constexpr uint32_t BAR_OUTRDY = BAR_STGFULL + 16;
constexpr uint32_t BAR_XREADY = BAR_OUTRDY + 16;
constexpr uint32_t BAR_SFULLC = BAR_XREADY + 32;
constexpr uint32_t BAR_TAB = BAR_SFULLC + 32;
constexpr uint32_t SCHED = BAR_TAB + 16;
constexpr int kMaxRing = 288;
constexpr int kTiles = 21;
constexpr int kTabBytes = (4 * (kMaxRing + kTiles) + 15) / 16 * 16;
constexpr int SMEM_BYTES = SCHED + kTabBytes - SB;
static_assert(SCHED % 16 == 0, "align");
static_assert(SMEM_BYTES <= 232448, "smem");

constexpr int kLead = 4;
constexpr int kLeadF = 2;
constexpr int kWPieces = 4;

__host__ __device__ constexpr int tile_chunk0(int j) {
    return (j == 0 || j == 7) ? 4 : j == 1 ? 0 : j == 2 ? 2 : j == 3 ? 6 : j == 4 ? 8 : j == 5 ? 10 : 11;
}
__host__ __device__ constexpr int tile_nchunk(int j) { return j == 5 ? 1 : 2; }
__host__ __device__ constexpr int korder(int j, int kk) {
    constexpr int oa[13] = {11, 12, 0, 1, 2, 3, 4, 5, 6, 7, 8, 9, 10};
    if (j == 0) return oa[kk];
    if (j >= 1 && j <= 4) return kk < 5 ? kNSC + kk : kk < 5 + kNSC ? kk - 5 : kk;
    return kk;
}
__host__ __device__ constexpr int xload(int j, int kk) {
    constexpr int xa[13] = {4, 5, -1, 6, 7, -1, 8, 9, -1, 10, -1, -1, -1};
    constexpr int xf[13] = {-1, -1, 4, 5, 6, 7, 8, 9, 10, 11, 12, -1, -1};
    return j == 0 ? xa[kk] : j == 7 ? xf[kk] : -1;
}
constexpr int kLastS = 3;
constexpr int kFirstS = 2;

enum { M_WK0 = 0, M_WK1, M_WK2, M_X0_R128, M_OUT_R128, M_X0_T2, M_X0_T1, M_OUT_T2, M_OUT_T1, M_COUNT };
struct Maps { CUtensorMap m[M_COUNT]; };

constexpr uint32_t E_HALF = 1u << 14, E_ISX = 1u << 19, E_EF = 1u << 20;
constexpr uint32_t T_ONE = 1u << 4, T_X0 = 1u << 5, T_BIAS = 1u << 6, T_STORE = 1u << 7, T_SREL = 1u << 11, T_XB = 1u << 14;
struct alignas(16) Sched { uint32_t e[kTabBytes / 4]; int n; };
constexpr uint32_t w_entry(int l, int k0, int atom, int kind) {
    return (uint32_t)((l * kD + k0) / 32) | (uint32_t)atom << 7 | (uint32_t)(M_WK0 + kind) << 11 |
           (kind == 2 ? E_HALF : 0u);
}
constexpr Sched make_sched() {
    Sched s{};
    int n = 0;
    int start[kL * 7] = {};
    for (int c = 0; c < 13; ++c) {
        if (c >= kNSC) {
            for (int q = 1; q <= 4; ++q) s.e[n - 5 + q] |= (uint32_t)q << 23 | (uint32_t)c << 27;
            s.e[n++] = (uint32_t)c << 7 | (uint32_t)M_X0_R128 << 11 | E_ISX;
        }
        s.e[n++] = w_entry(0, c * 64, tile_chunk0(3), 0);
        s.e[n++] = w_entry(0, c * 64, tile_chunk0(1), 0);
        s.e[n++] = w_entry(0, c * 64, tile_chunk0(2), 0);
    }
    for (int l = 0; l < kL; ++l) {
        for (int jj = 0; jj < 7; ++jj) {
            start[l * 7 + jj] = n;
            if (l == 0 && jj >= 1 && jj <= 3) continue;
            const int j = (l == 0 && jj == 0) ? 7 : jj;
            const int atom = tile_chunk0(j);
            if (j == 5) {
                for (int kk = 0; kk < 13; kk += 2) s.e[n++] = w_entry(l, kk * 64, atom, kk < 12 ? 1 : 2);
                continue;
            }
            for (int kk = 0; kk < 13; ++kk) {
                const int c = korder(j, kk);
                const int xc = xload(j, kk);
                if (xc >= 0) {
                    uint32_t e = (uint32_t)xc << 7 | (uint32_t)(j == 7 ? M_X0_R128 : M_OUT_R128) << 11 | E_ISX;
                    if (j == 7) e |= E_EF;
                    else e |= (uint32_t)((xc - 4) / 2 + 1) << 15 | (uint32_t)((l - 1) & 1) << 18;
                    s.e[n++] = e;
                }
                s.e[n++] = w_entry(l, c * 64, atom, 0);
            }
        }
    }
    s.n = n;
    for (int l = 0; l < kL - 1; ++l) {
        const int lo = l == 0 ? start[4] : start[l * 7 + 1], hi = start[l * 7 + 6];
        for (int q = 0; q < kWPieces; ++q) {
            int at = lo + (hi - lo) * q / kWPieces;
            while (s.e[at] & E_ISX) ++at;
            s.e[at] |= (uint32_t)(l + 1) << 21 | (uint32_t)q << 15;
        }
    }
    for (int t = 0; t < kTiles; ++t) {
        const int l = t / 7;
        const int l0order[7] = {3, 1, 2, 0, 4, 5, 6};
        const int j = l == 0 ? l0order[t] : t % 7;
        uint32_t e = (uint32_t)tile_chunk0(j) | (uint32_t)l << 12;
        if (j == 5) e |= T_ONE;
        if (l > 0 || t == 0) e |= T_X0;
        if (l > 0 || (t != 1 && t != 2)) e |= T_BIAS;
        if (t == 0) e |= T_XB;
        if (j != 6 || l == kL - 1) e |= T_STORE;
        if (l < kL - 1 && (j == 0 || (j >= 3 && j <= 5))) e |= (uint32_t)(j == 0 ? 1 : j - 1) << 8;
        if (j == 6 && l < kL - 1) e |= T_SREL;
        s.e[kMaxRing + t] = e;
    }
    return s;
}
constexpr Sched kSchedHost = make_sched();
constexpr int kRingLen = kSchedHost.n;
static_assert(kRingLen <= kMaxRing, "sched");
__device__ const Sched g_sched = make_sched();
static_assert((kSchedHost.e[0] | kSchedHost.e[1] | kSchedHost.e[2] | kSchedHost.e[3] | kSchedHost.e[4] | kSchedHost.e[5] |
               kSchedHost.e[6] | kSchedHost.e[7]) < (1u << 11), "the first ring entries are plain W slots");

__device__ __forceinline__ uint32_t smem_u32(const void* p) {
    return (uint32_t)__cvta_generic_to_shared(p);
}
__device__ __forceinline__ bool elect_one() {
    uint32_t p;
    asm volatile("{\n.reg .pred p;\nelect.sync _|p, 0xffffffff;\nselp.u32 %0, 1, 0, p;\n}" : "=r"(p));
    return p != 0;
}
__device__ __forceinline__ void mbar_init(uint32_t a, uint32_t cnt) {
    asm volatile("mbarrier.init.shared::cta.b64 [%0], %1;" ::"r"(a), "r"(cnt) : "memory");
}
__device__ __forceinline__ void mbar_expect_tx(uint32_t a, uint32_t bytes) {
    asm volatile("mbarrier.arrive.expect_tx.shared::cta.b64 _, [%0], %1;" ::"r"(a), "r"(bytes) : "memory");
}
__device__ __forceinline__ void mbar_arrive(uint32_t a) {
    asm volatile("mbarrier.arrive.shared::cta.b64 _, [%0];" ::"r"(a) : "memory");
}
__device__ __forceinline__ void mbar_wait(uint32_t a, uint32_t parity) {
    asm volatile(
        "{\n.reg .pred p, q;\n.reg .u32 n;\n"
        "mov.u32 n, 0;\n"
        "WAIT_%=:\n"
        "mbarrier.try_wait.parity.shared::cta.b64 p, [%0], %1;\n"
        "@p bra DONE_%=;\n"
        "add.u32 n, n, 1;\n"
        "setp.gt.u32 q, n, 16777216;\n"
        "@q trap;\n"
        "bra WAIT_%=;\n"
        "DONE_%=:\n}"
        ::"r"(a), "r"(parity) : "memory");
}
__device__ __forceinline__ void tma_load_plain(uint32_t dst, const CUtensorMap* tm, int row, int atom, uint32_t bar) {
    asm volatile(
        "cp.async.bulk.tensor.3d.shared::cluster.global.mbarrier::complete_tx::bytes "
        "[%0], [%1, {%3, %4, %5}], [%2];"
        ::"r"(dst), "l"(tm), "r"(bar), "r"(0), "r"(row), "r"(atom) : "memory");
}
__device__ __forceinline__ uint32_t mbar_test(uint32_t a, uint32_t parity) {
    uint32_t ok;
    asm volatile("{\n.reg .pred p;\nmbarrier.test_wait.parity.shared::cta.b64 p, [%1], %2;\nselp.u32 %0, 1, 0, p;\n}"
                 : "=r"(ok) : "r"(a), "r"(parity) : "memory");
    return ok;
}
__device__ __forceinline__ void fence_proxy_async_smem() {
    asm volatile("fence.proxy.async.shared::cta;" ::: "memory");
}
__device__ __forceinline__ void fence_proxy_async_global() {
    asm volatile("fence.proxy.async.global;" ::: "memory");
}
__device__ __forceinline__ uint64_t policy_evict_first() {
    uint64_t p;
    asm volatile("createpolicy.fractional.L2::evict_first.b64 %0, 1.0;" : "=l"(p));
    return p;
}
__device__ __forceinline__ uint64_t policy_evict_normal() {
    uint64_t p;
    asm volatile("createpolicy.fractional.L2::evict_normal.b64 %0, 1.0;" : "=l"(p));
    return p;
}
__device__ __forceinline__ void tma_load(uint32_t dst, const CUtensorMap* tm, int row, int atom, uint32_t bar,
                                         uint64_t pol) {
    asm volatile(
        "cp.async.bulk.tensor.3d.shared::cluster.global.mbarrier::complete_tx::bytes.L2::cache_hint "
        "[%0], [%1, {%3, %4, %5}], [%2], %6;"
        ::"r"(dst), "l"(tm), "r"(bar), "r"(0), "r"(row), "r"(atom), "l"(pol) : "memory");
}
__device__ __forceinline__ void tma_store(const CUtensorMap* tm, int row, int atom, uint32_t src, uint64_t pol) {
    asm volatile("cp.async.bulk.tensor.3d.global.shared::cta.bulk_group.L2::cache_hint [%0, {%2, %3, %4}], [%1], %5;"
                 ::"l"(tm), "r"(src), "r"(0), "r"(row), "r"(atom), "l"(pol) : "memory");
}
__device__ __forceinline__ void bulk_load(uint32_t dst, const void* src, uint32_t bytes, uint32_t bar) {
    asm volatile(
        "cp.async.bulk.shared::cluster.global.mbarrier::complete_tx::bytes [%0], [%1], %2, [%3];"
        ::"r"(dst), "l"(src), "r"(bytes), "r"(bar) : "memory");
}
__device__ __forceinline__ void prefetch_l2(const void* p, uint32_t bytes) {
    asm volatile("cp.async.bulk.prefetch.L2.global [%0], %1;" ::"l"(p), "r"(bytes) : "memory");
}
__device__ __forceinline__ void bulk_commit() { asm volatile("cp.async.bulk.commit_group;" ::: "memory"); }
__device__ __forceinline__ void bulk_wait_read0() { asm volatile("cp.async.bulk.wait_group.read 0;" ::: "memory"); }
__device__ __forceinline__ void bulk_wait0() { asm volatile("cp.async.bulk.wait_group 0;" ::: "memory"); }
__device__ __forceinline__ void prefetch_tmap(const CUtensorMap* tm) {
    asm volatile("prefetch.tensormap [%0];" ::"l"(tm) : "memory");
}

__device__ __forceinline__ uint32_t pack_bf16(float lo, float hi) {
    uint32_t r;
    asm("cvt.rn.bf16x2.f32 %0, %1, %2;" : "=r"(r) : "f"(hi), "f"(lo));
    return r;
}
__device__ __forceinline__ uint32_t add_bf16x2(uint32_t a, uint32_t b) {
    uint32_t r;
    asm("add.rn.bf16x2 %0, %1, %2;" : "=r"(r) : "r"(a), "r"(b));
    return r;
}
__device__ __forceinline__ uint32_t fma_bf16x2(uint32_t a, uint32_t b, uint32_t c) {
    uint32_t r;
    asm("fma.rn.bf16x2 %0, %1, %2, %3;" : "=r"(r) : "r"(a), "r"(b), "r"(c));
    return r;
}

__device__ __forceinline__ void wgmma_fence() { asm volatile("wgmma.fence.sync.aligned;" ::: "memory"); }
__device__ __forceinline__ void wgmma_commit() { asm volatile("wgmma.commit_group.sync.aligned;" ::: "memory"); }
template <int N>
__device__ __forceinline__ void wgmma_wait() {
    asm volatile("wgmma.wait_group.sync.aligned %0;" ::"n"(N) : "memory");
}

#define ACC8(o) "+f"(d[o + 0]), "+f"(d[o + 1]), "+f"(d[o + 2]), "+f"(d[o + 3]), "+f"(d[o + 4]), "+f"(d[o + 5]), "+f"(d[o + 6]), "+f"(d[o + 7])
#define REGS32 "%0,%1,%2,%3,%4,%5,%6,%7,%8,%9,%10,%11,%12,%13,%14,%15,%16,%17,%18,%19,%20,%21,%22,%23,%24,%25,%26,%27,%28,%29,%30,%31"
#define REGS64 REGS32 ",%32,%33,%34,%35,%36,%37,%38,%39,%40,%41,%42,%43,%44,%45,%46,%47,%48,%49,%50,%51,%52,%53,%54,%55,%56,%57,%58,%59,%60,%61,%62,%63"

#define DESC_HI_STR "0x40000040"
constexpr uint32_t DESC_LO_B = (8192u >> 4) << 16;
constexpr uint32_t DESC_LO_A = 1u << 16;

template <int SCALE_D, uint32_t BOFF>
__device__ __forceinline__ void wgmma_rs_n128(float (&d)[64], uint32_t a0, uint32_t a1, uint32_t a2, uint32_t a3,
                                              uint32_t blo) {
    asm volatile(
        "{\n.reg .pred p;\n.reg .b32 lo;\n.reg .b64 db;\nsetp.ne.b32 p, %69, 0;\n"
        "add.u32 lo, %68, %70;\nmov.b64 db, {lo, " DESC_HI_STR "};\n"
        "wgmma.mma_async.sync.aligned.m64n128k16.f32.bf16.bf16 {" REGS64 "}, {%64,%65,%66,%67}, db, p, 1, 1, 1;\n}"
        : ACC8(0), ACC8(8), ACC8(16), ACC8(24), ACC8(32), ACC8(40), ACC8(48), ACC8(56)
        : "r"(a0), "r"(a1), "r"(a2), "r"(a3), "r"(blo), "n"(SCALE_D), "n"(BOFF));
}
template <int SCALE_D, uint32_t AOFF, uint32_t BOFF>
__device__ __forceinline__ void wgmma_ss_n128(float (&d)[64], uint32_t alo, uint32_t blo) {
    asm volatile(
        "{\n.reg .pred p;\n.reg .b32 lo, lo2;\n.reg .b64 da, db;\nsetp.ne.b32 p, %66, 0;\n"
        "add.u32 lo, %64, %67;\nmov.b64 da, {lo, " DESC_HI_STR "};\n"
        "add.u32 lo2, %65, %68;\nmov.b64 db, {lo2, " DESC_HI_STR "};\n"
        "wgmma.mma_async.sync.aligned.m64n128k16.f32.bf16.bf16 {" REGS64 "}, da, db, p, 1, 1, 0, 1;\n}"
        : ACC8(0), ACC8(8), ACC8(16), ACC8(24), ACC8(32), ACC8(40), ACC8(48), ACC8(56)
        : "r"(alo), "r"(blo), "n"(SCALE_D), "n"(AOFF), "n"(BOFF));
}
template <int SCALE_D, uint32_t BOFF>
__device__ __forceinline__ void wgmma_rs_n64(float (&d)[64], uint32_t a0, uint32_t a1, uint32_t a2, uint32_t a3,
                                             uint32_t blo) {
    asm volatile(
        "{\n.reg .pred p;\n.reg .b32 lo;\n.reg .b64 db;\nsetp.ne.b32 p, %37, 0;\n"
        "add.u32 lo, %36, %38;\nmov.b64 db, {lo, " DESC_HI_STR "};\n"
        "wgmma.mma_async.sync.aligned.m64n64k16.f32.bf16.bf16 {" REGS32 "}, {%32,%33,%34,%35}, db, p, 1, 1, 1;\n}"
        : ACC8(0), ACC8(8), ACC8(16), ACC8(24)
        : "r"(a0), "r"(a1), "r"(a2), "r"(a3), "r"(blo), "n"(SCALE_D), "n"(BOFF));
}
template <int SCALE_D, uint32_t AOFF, uint32_t BOFF>
__device__ __forceinline__ void wgmma_ss_n64(float (&d)[64], uint32_t alo, uint32_t blo) {
    asm volatile(
        "{\n.reg .pred p;\n.reg .b32 lo, lo2;\n.reg .b64 da, db;\nsetp.ne.b32 p, %34, 0;\n"
        "add.u32 lo, %32, %35;\nmov.b64 da, {lo, " DESC_HI_STR "};\n"
        "add.u32 lo2, %33, %36;\nmov.b64 db, {lo2, " DESC_HI_STR "};\n"
        "wgmma.mma_async.sync.aligned.m64n64k16.f32.bf16.bf16 {" REGS32 "}, da, db, p, 1, 1, 0, 1;\n}"
        : ACC8(0), ACC8(8), ACC8(16), ACC8(24)
        : "r"(alo), "r"(blo), "n"(SCALE_D), "n"(AOFF), "n"(BOFF));
}
template <int T, uint32_t OFF>
__device__ __forceinline__ void ldsm4x(uint32_t base, uint32_t& r0, uint32_t& r1, uint32_t& r2, uint32_t& r3) {
    asm volatile("{\n.reg .b32 ad;\nxor.b32 ad, %4, %5;\n"
                 "ldmatrix.sync.aligned.m8n8.x4.shared.b16 {%0,%1,%2,%3}, [ad + %6];\n}"
                 : "=r"(r0), "=r"(r1), "=r"(r2), "=r"(r3) : "r"(base), "n"(T * 32), "n"(OFF) : "memory");
}
template <int T, uint32_t OFF>
__device__ __forceinline__ void stsm4x(uint32_t base, uint32_t r0, uint32_t r1, uint32_t r2, uint32_t r3) {
    asm volatile("{\n.reg .b32 ad;\nxor.b32 ad, %0, %5;\n"
                 "stmatrix.sync.aligned.m8n8.x4.shared.b16 [ad + %6], {%1,%2,%3,%4};\n}"
                 ::"r"(base), "r"(r0), "r"(r1), "r"(r2), "r"(r3), "n"(T * 32), "n"(OFF) : "memory");
}
template <uint32_t OFF>
__device__ __forceinline__ void ldsm16(uint32_t base, uint32_t* r) {
    ldsm4x<0, OFF>(base, r[0], r[1], r[2], r[3]);
    ldsm4x<1, OFF>(base, r[4], r[5], r[6], r[7]);
    ldsm4x<2, OFF>(base, r[8], r[9], r[10], r[11]);
    ldsm4x<3, OFF>(base, r[12], r[13], r[14], r[15]);
}
template <uint32_t OFF>
__device__ __forceinline__ void stsm16(uint32_t base, const uint32_t* r) {
    stsm4x<0, OFF>(base, r[0], r[1], r[2], r[3]);
    stsm4x<1, OFF>(base, r[4], r[5], r[6], r[7]);
    stsm4x<2, OFF>(base, r[8], r[9], r[10], r[11]);
    stsm4x<3, OFF>(base, r[12], r[13], r[14], r[15]);
}
template <uint32_t OFF>
__device__ __forceinline__ uint32_t lds32x(uint32_t base) {
    uint32_t v;
    asm volatile("ld.shared.b32 %0, [%1 + %2];" : "=r"(v) : "r"(base), "n"(OFF) : "memory");
    return v;
}


__host__ __device__ constexpr int tile_slots(int j) { return j == 5 ? 7 : j == 0 ? 20 : j == 7 ? 22 : 13; }
constexpr int kFusedLen = 48;
constexpr int kLoopLen = 92;
static_assert(kLoopLen % kNS == 4 && kFusedLen + tile_slots(7) + 2 * kLoopLen + 33 == kRingLen, "ring layout");
__host__ __device__ constexpr int tile_pos(int j) {
    constexpr int order[8] = {7, 4, 5, 6, 0, 1, 2, 3};
    int pos = kFusedLen;
    for (int i = 0; order[i] != j; ++i) pos += tile_slots(order[i]);
    return pos;
}
__host__ __device__ constexpr int step_pos(int j, int kk) {
    int pos = tile_pos(j) + kk;
    for (int i = 0; i < kk; ++i) pos += (j != 5 && xload(j, i) >= 0) ? 1 : 0;
    return pos;
}

struct Ctx {
    uint32_t it;
    uint32_t sx;
    uint32_t par[2];
    uint32_t tb;
    uint32_t wg;
    uint32_t tcnt;
    uint32_t bb;
    bool lane0;
};

__device__ __forceinline__ void release_slot(const Ctx& c, uint32_t slot) {
    if (c.lane0) mbar_arrive(BAR_EMPTY + slot * 8);
}
__device__ __forceinline__ void release_after_ldsm(const Ctx& c, uint32_t slot, const uint32_t* r) {
    asm volatile(
        "{\n.reg .pred p, q;\n.reg .b32 x;\n"
        "lop3.b32 x, %2, %3, %4, 0x96;\n"
        "xor.b32 x, x, %5;\n"
        "setp.ne.u32 p, x, 0x5bd1e995;\n"
        "vote.sync.any.pred q, p, 0xffffffff;\n"
        "vote.sync.any.pred p, !p, 0xffffffff;\n"
        "or.pred p, p, q;\n"
        "setp.ne.and.u32 p, %1, 0, p;\n"
        "@p mbarrier.arrive.shared::cta.b64 _, [%0];\n}"
        ::"r"(BAR_EMPTY + slot * 8), "r"((uint32_t)c.lane0), "r"(r[3]), "r"(r[7]), "r"(r[11]), "r"(r[15]) : "memory");
}
__device__ __forceinline__ uint32_t wait_slot(Ctx& cx) {
    const uint32_t slot = cx.it & (kNS - 1);
    mbar_wait(BAR_FULL + slot * 8, (cx.it / kNS) & 1);
    cx.it++;
    return slot;
}
template <int POS>
__device__ __forceinline__ uint32_t slot_at(const Ctx& cx) { return (uint32_t)(POS & (kNS - 1)) ^ cx.sx; }
template <int POS>
__device__ __forceinline__ uint32_t par_at(const Ctx& cx) { return (uint32_t)((POS / kNS) & 1) ^ cx.par[(POS >> 2) & 1]; }
__device__ __forceinline__ void set_pass(Ctx& cx, uint32_t pass) {
    const uint32_t off = pass * kLoopLen;
    cx.sx = off & 4;
    cx.par[0] = (off / kNS) & 1;
    cx.par[1] = ((off + 4) / kNS) & 1;
}
__device__ __forceinline__ void publish_stage(Ctx& cx) {
    fence_proxy_async_smem();
    __syncwarp();
    if (cx.lane0) mbar_arrive(BAR_OUTRDY + cx.wg * 8);
    cx.tcnt++;
}

template <uint32_t OFF>
__device__ __forceinline__ void ld_bias(const Ctx& cx, uint32_t* b) {
    ldsm4x<0, BIAS + OFF>(cx.bb, b[0], b[1], b[2], b[3]);
    ldsm4x<0, BIAS + OFF + 64>(cx.bb, b[4], b[5], b[6], b[7]);
}
template <int H>
__device__ __forceinline__ void pack_bias(const float (&acc)[64], const uint32_t* b, uint32_t* p) {
#pragma unroll
    for (int i = 0; i < 16; ++i)
        p[i] = add_bf16x2(pack_bf16(acc[32 * H + 2 * i], acc[32 * H + 2 * i + 1]), b[i >> 1]);
}
template <uint32_t BOFF, uint32_t XOFF>
__device__ __forceinline__ void epi_self(Ctx& cx, const float (&acc)[64]) {
    uint32_t b[16], p[32], x[32];
    ld_bias<BOFF>(cx, b);
    ld_bias<BOFF + 128>(cx, b + 8);
    pack_bias<0>(acc, b, p);
    ldsm16<XOFF>(cx.tb, x);
    pack_bias<1>(acc, b + 8, p + 16);
    ldsm16<XOFF + 8192>(cx.tb, x + 16);
#pragma unroll
    for (int i = 0; i < 32; ++i) x[i] = fma_bf16x2(x[i], p[i], x[i]);
    if constexpr (XOFF != STG) {
        mbar_wait(BAR_STGFULL + cx.wg * 8, cx.tcnt & 1);
    }
    stsm16<STG>(cx.tb, x);
    stsm16<STG + 8192>(cx.tb, x + 16);
    publish_stage(cx);
}

template <bool N64, bool FIRST, int C, int T, uint32_t BOFF>
__device__ __forceinline__ void mma_k16(const Ctx& cx, uint32_t (&a)[kNRC][16], float (&acc)[64], const uint32_t blo) {
    constexpr int F = FIRST ? 0 : 1;
    if constexpr (C < kNSC) {
        const uint32_t alo = cx.wg * (kWgStride >> 4);
        constexpr uint32_t A0 = DESC_LO_A + ((SREG + C * 8192) >> 4) + 2 * T;
        if constexpr (N64) wgmma_ss_n64<F, A0, BOFF + 128 * T>(acc, alo, blo);
        else wgmma_ss_n128<F, A0, BOFF + 128 * T>(acc, alo, blo);
    } else {
        uint32_t(&r)[16] = a[C - kNSC];
        if constexpr (N64) wgmma_rs_n64<F, BOFF + 128 * T>(acc, r[4 * T], r[4 * T + 1], r[4 * T + 2], r[4 * T + 3], blo);
        else wgmma_rs_n128<F, BOFF + 128 * T>(acc, r[4 * T], r[4 * T + 1], r[4 * T + 2], r[4 * T + 3], blo);
    }
}

constexpr uint32_t B0 = DESC_LO_B + (RING >> 4);

__host__ __device__ constexpr int tile_steps(int j) { return j == 5 ? 7 : 13; }
__host__ __device__ constexpr int sync_step(int j) {
    return j == 7 ? 10 : tile_steps(j) - 1 - (j == 5 ? kLeadF : kLead);
}
__host__ __device__ constexpr bool prewait(int j, int kk) {
    return kk >= 1 && kk < tile_steps(j) && (j == 5 || xload(j, kk) < 0) && !(j == 7 && kk <= 4);
}

template <int J, int KK>
__device__ __forceinline__ void k_step(Ctx& cx, uint32_t (&a)[kNRC][16], float (&acc)[64], const int l, uint32_t& prev,
                                       uint32_t& pend, const float (&accB)[64], const float (&accC)[64]) {
    constexpr bool kN64 = (tile_nchunk(J) == 1);
    constexpr int kSteps = tile_steps(J);
    if constexpr (KK < kSteps) {
        constexpr int C = kN64 ? 2 * KK : korder(J, KK);
        if constexpr (KK == sync_step(J)) {
            if (cx.wg == 1) asm volatile("bar.sync 1, 256;" ::: "memory");
        }
        constexpr int XC = kN64 ? -1 : xload(J, KK);
        uint32_t xslot = 0;
        if constexpr (XC >= 0) {
            xslot = slot_at<step_pos(J, KK)>(cx);
            mbar_wait(BAR_FULL + xslot * 8, par_at<step_pos(J, KK)>(cx));
            ldsm16<RING>(cx.tb + xslot * kSlot - cx.wg * (kWgStride - 8192), a[XC - kNSC]);
        }
        if constexpr (J == 0 && KK == kFirstS) mbar_wait(BAR_SFULL + cx.wg * 8, (l - 1) & 1);
        constexpr int POS = step_pos(J, KK) + (XC >= 0 ? 1 : 0);
        const uint32_t slot = slot_at<POS>(cx);
        if constexpr (prewait(J, KK)) {
            if (!__all_sync(0xffffffffu, pend)) mbar_wait(BAR_FULL + slot * 8, par_at<POS>(cx));
        } else {
            mbar_wait(BAR_FULL + slot * 8, par_at<POS>(cx));
        }
        const uint32_t blo = slot * (kSlot >> 4);
        wgmma_fence();
        mma_k16<kN64, KK == 0, C, 0, B0>(cx, a, acc, blo);
        if constexpr (KK == 0 && J != 7) publish_stage(cx);
        mma_k16<kN64, false, C, 1, B0>(cx, a, acc, blo);
        mma_k16<kN64, false, C, 2, B0>(cx, a, acc, blo);
        if constexpr (!kN64 && prewait(J, KK + 1)) pend = mbar_test(BAR_FULL + slot_at<POS + 1>(cx) * 8, par_at<POS + 1>(cx));
        mma_k16<kN64, false, C, 3, B0>(cx, a, acc, blo);
        if constexpr (kN64 && C + 1 < 13) {
            mma_k16<true, false, C + 1, 0, B0 + 512>(cx, a, acc, blo);
            mma_k16<true, false, C + 1, 1, B0 + 512>(cx, a, acc, blo);
            pend = mbar_test(BAR_FULL + slot_at<POS + 1>(cx) * 8, par_at<POS + 1>(cx));
            mma_k16<true, false, C + 1, 2, B0 + 512>(cx, a, acc, blo);
            mma_k16<true, false, C + 1, 3, B0 + 512>(cx, a, acc, blo);
        }
        wgmma_commit();
        if constexpr (XC >= 0) release_after_ldsm(cx, xslot, a[XC - kNSC]);
        if constexpr (KK == kSteps - 1) {
            if (cx.wg == 0) asm volatile("bar.arrive 1, 256;" ::: "memory");
        }
        if constexpr (J == 7 && KK <= 3) {
            if constexpr (KK == 1) epi_self<256, SREG>(cx, accB);
            if constexpr (KK == 3) epi_self<512, SREG + 2 * 8192>(cx, accC);
            if constexpr (KK == 2) {
                wgmma_wait<1>();
                release_slot(cx, (prev - 1) & (kNS - 1));
                release_slot(cx, prev);
            }
            if constexpr (KK == 3) {
                wgmma_wait<1>();
                release_slot(cx, prev);
            }
        } else if constexpr (KK > 0) {
            wgmma_wait<1>();
            release_slot(cx, prev);
            if constexpr (J == 6 && KK == kLastS + 1) {
                if (cx.lane0) mbar_arrive(BAR_SFREE + cx.wg * 8);
            }
        }
        prev = slot;
        k_step<J, KK + 1>(cx, a, acc, l, prev, pend, accB, accC);
    }
}

template <int J>
__device__ __forceinline__ void epi_tile(const Ctx& cx, uint32_t (&a)[kNRC][16], const float (&acc)[64],
                                         const uint32_t* b, const int l) {
    constexpr int C = tile_chunk0(J);
    constexpr int NH = tile_nchunk(J);
    uint32_t p[32];
    if constexpr (C < kNSC) {
        uint32_t xl[16], x0[16];
        pack_bias<0>(acc, b, p);
        pack_bias<1>(acc, b + 8, p + 16);
        asm volatile("" ::"r"(p[0]), "r"(p[2]), "r"(p[4]), "r"(p[6]), "r"(p[8]), "r"(p[10]), "r"(p[12]), "r"(p[14]),
                     "r"(p[17]), "r"(p[19]), "r"(p[21]), "r"(p[23]), "r"(p[25]), "r"(p[27]), "r"(p[29]), "r"(p[31]) : "memory");
        __syncwarp();
        ldsm16<SREG + C * 8192>(cx.tb, xl);
        ldsm16<STG>(cx.tb, x0);
#pragma unroll
        for (int i = 0; i < 16; ++i) xl[i] = fma_bf16x2(x0[i], p[i], xl[i]);
        stsm16<STG>(cx.tb, xl);
        __syncwarp();
        ldsm16<SREG + (C + 1) * 8192>(cx.tb, xl);
        ldsm16<STG + 8192>(cx.tb, x0);
#pragma unroll
        for (int i = 0; i < 16; ++i) xl[i] = fma_bf16x2(x0[i], p[16 + i], xl[i]);
        stsm16<STG + 8192>(cx.tb, xl);
    } else {
        uint32_t o[32];
        if (J <= 3 || (J != 7 && l != 0)) {
            pack_bias<0>(acc, b, p);
            ldsm16<STG>(cx.tb, o);
            if constexpr (NH == 2) {
                pack_bias<1>(acc, b + 8, p + 16);
                ldsm16<STG + 8192>(cx.tb, o + 16);
            }
#pragma unroll
            for (int i = 0; i < 16 * NH; ++i) o[i] = fma_bf16x2(o[i], p[i], a[C - kNSC + i / 16][i % 16]);
        } else {
            pack_bias<0>(acc, b, p);
            if constexpr (NH == 2) pack_bias<1>(acc, b + 8, p + 16);
#pragma unroll
            for (int i = 0; i < 16 * NH; ++i)
                o[i] = fma_bf16x2(a[C - kNSC + i / 16][i % 16], p[i], a[C - kNSC + i / 16][i % 16]);
        }
        if constexpr (J == 6) {
#pragma unroll
            for (int i = 0; i < 32; ++i) a[C - kNSC + i / 16][i % 16] = o[i];
        }
        if (J != 6 || l == kL - 1) {
            stsm16<STG>(cx.tb, o);
            if constexpr (NH == 2) stsm16<STG + 8192>(cx.tb, o + 16);
        }
    }
}

template <int J>
__device__ __forceinline__ void do_tile(Ctx& cx, uint32_t (&a)[kNRC][16], float (&acc)[64], const int l,
                                        const float (&accB)[64], const float (&accC)[64]) {
    uint32_t prev = 0, pend = 0;
    k_step<J, 0>(cx, a, acc, l, prev, pend, accB, accC);
    mbar_wait(BAR_STGFULL + cx.wg * 8, cx.tcnt & 1);
    uint32_t b[16];
    ld_bias<0>(cx, b);
    if constexpr (tile_nchunk(J) == 2) ld_bias<128>(cx, b + 8);
    wgmma_wait<0>();
    release_slot(cx, prev);
    epi_tile<J>(cx, a, acc, b, l);
}

__device__ __forceinline__ void ss_group(Ctx& cx, float (&acc)[64], const uint32_t alo, uint32_t& prev, const bool rel) {
    const uint32_t slot = wait_slot(cx);
    const uint32_t blo = slot * (kSlot >> 4);
    wgmma_fence();
    wgmma_ss_n128<1, DESC_LO_A, B0>(acc, alo, blo);
    wgmma_ss_n128<1, DESC_LO_A + 2, B0 + 128>(acc, alo, blo);
    wgmma_ss_n128<1, DESC_LO_A + 4, B0 + 256>(acc, alo, blo);
    wgmma_ss_n128<1, DESC_LO_A + 6, B0 + 384>(acc, alo, blo);
    wgmma_commit();
    wgmma_wait<1>();
    if (rel) release_slot(cx, prev);
    prev = slot;
}

__device__ __forceinline__ void fused_pass(Ctx& cx, float (&accD)[64], float (&accB)[64], float (&accC)[64]) {
#pragma unroll
    for (int i = 0; i < 64; ++i) { accD[i] = 0.f; accB[i] = 0.f; accC[i] = 0.f; }
    uint32_t prev = 0, xslot = 0;
#pragma unroll 1
    for (int c = 0; c < 13; ++c) {
        uint32_t alo;
        const uint32_t xprev = xslot;
        if (c < kNSC) {
            mbar_wait(BAR_SFULLC + c * 8, 0);
            alo = (SREG + c * 8192 + cx.wg * kWgStride) >> 4;
        } else {
            xslot = wait_slot(cx);
            alo = (RING + xslot * kSlot + cx.wg * 8192) >> 4;
        }
        ss_group(cx, accD, alo, prev, c > 0);
        if (c > kNSC) release_slot(cx, xprev);
        if (c == 11 && cx.wg == 1) asm volatile("bar.sync 1, 256;" ::: "memory");
        ss_group(cx, accB, alo, prev, true);
        if (c == 12 && cx.wg == 0) asm volatile("bar.arrive 1, 256;" ::: "memory");
        ss_group(cx, accC, alo, prev, true);
    }
    mbar_wait(BAR_STGFULL + cx.wg * 8, 0);
    epi_self<0, STG>(cx, accD);
    wgmma_wait<0>();
    release_slot(cx, prev);
    release_slot(cx, xslot);
}

__device__ __forceinline__ void load_s_chunk(const Maps& maps, int row0, int c, uint64_t pol) {
    const uint32_t bar = BAR_SFULLC + c * 8;
    mbar_expect_tx(bar, 16384);
    tma_load(SREG + c * 8192, &maps.m[M_X0_T1], row0, c, bar, pol);
    tma_load(SREG + kWgStride + c * 8192, &maps.m[M_X0_T1], row0 + 64, c, bar, pol);
}

__global__ void __launch_bounds__(384, 1)
dcn_kernel(const __grid_constant__ Maps maps, const __nv_bfloat16* __restrict__ bs,
           const __nv_bfloat16* __restrict__ ws, const __nv_bfloat16* __restrict__ x0) {
    extern __shared__ uint8_t smem_raw[];
    if (smem_u32(smem_raw) != SB) __trap();
    const int warp = __shfl_sync(0xffffffffu, threadIdx.x >> 5, 0);
    const int lane = threadIdx.x & 31;
    const int row0 = blockIdx.x * kBM;
    constexpr uint32_t kWShare = kD * kD * 2 / 128;

    if (threadIdx.x == 288) {
        for (int j = 0; j < kNSC; ++j) mbar_init(BAR_SFULLC + j * 8, 1);
        fence_proxy_async_smem();
        load_s_chunk(maps, row0, 0, policy_evict_first());
    }
    if (threadIdx.x == 256) {
        for (int s = 0; s < kNS; ++s) {
            mbar_init(BAR_FULL + s * 8, 1);
            mbar_init(BAR_EMPTY + s * 8, 8);
        }
        fence_proxy_async_smem();
#pragma unroll
        for (int it = 0; it < kNS; ++it) {
            mbar_expect_tx(BAR_FULL + it * 8, 16384);
            tma_load_plain(RING + it * kSlot, &maps.m[M_WK0], (it / 3) * 64, tile_chunk0(it % 3 == 0 ? 3 : it % 3),
                           BAR_FULL + it * 8);
        }
    }
    if (threadIdx.x == 0) {
        for (int w = 0; w < 2; ++w) {
            mbar_init(BAR_SFULL + w * 8, 1);
            mbar_init(BAR_SFREE + w * 8, 4);
            mbar_init(BAR_STGFULL + w * 8, 1);
            mbar_init(BAR_OUTRDY + w * 8, 4);
        }
        for (int j = 0; j < 4; ++j) mbar_init(BAR_XREADY + j * 8, 2);
        mbar_init(BAR_TAB, 1);
        fence_proxy_async_smem();
        mbar_expect_tx(BAR_TAB, kTabBytes);
        bulk_load(SCHED, g_sched.e, kTabBytes, BAR_TAB);
    }
    if (warp == 10 && lane < M_COUNT) prefetch_tmap(&maps.m[lane]);
    __syncthreads();

    if (warp >= 8) {
        asm volatile("setmaxnreg.dec.sync.aligned.u32 24;");
        if (warp == 8 || warp == 11) {
            const uint64_t pol_x = policy_evict_first();
            const uint64_t pol_n = policy_evict_normal();
            mbar_wait(BAR_TAB, 0);
#pragma unroll 1
            for (uint32_t it = kNS + (warp == 8 ? 0 : 1); it < (uint32_t)kRingLen; it += 2) {
                const uint32_t e = lds32x<SCHED>(it * 4);
                const uint32_t slot = it & (kNS - 1);
                const uint32_t xw = (e >> 15) & 7;
                if (xw && (e & E_ISX)) mbar_wait(BAR_XREADY - 8 + xw * 8, (e >> 18) & 1);
                mbar_wait(BAR_EMPTY + slot * 8, ((it / kNS) & 1) ^ 1);
                if (elect_one()) {
                    const uint32_t fb = BAR_FULL + slot * 8;
                    mbar_expect_tx(fb, (e & E_HALF) ? 8192 : 16384);
                    const CUtensorMap* tm = &maps.m[(e >> 11) & 7];
                    if (e & E_ISX) {
                        tma_load(RING + slot * kSlot, tm, row0, (e >> 7) & 15, fb, (e & E_EF) ? pol_x : pol_n);
                    } else {
                        tma_load_plain(RING + slot * kSlot, tm, (int)(e & 127) * 32, (e >> 7) & 15, fb);
                    }
                    const uint32_t wpf = (e >> 21) & 3;
                    if (wpf)
                        prefetch_l2((const char*)ws + wpf * (kD * kD * 2) + blockIdx.x * kWShare + ((e >> 15) & 15) * (kWShare / kWPieces),
                                    kWShare / kWPieces);
                }
                __syncwarp();
                const uint32_t job = (e >> 23) & 15;
                if (job) {
                    const char* pa =
                        (const char*)x0 + (uint32_t)((row0 + (job - 1) * 32 + lane) * (kD * 2) + (e >> 27) * 128);
                    asm volatile("prefetch.global.L2 [%0];" ::"l"(pa));
                }
            }
        } else if (lane == 0) {
            const uint64_t pol_x = policy_evict_first();
            const uint64_t pol_n = policy_evict_normal();
            if (warp == 9) {
                load_s_chunk(maps, row0, 1, pol_x);
#pragma unroll 1
                for (int c = 2; c < kNSC; ++c) {
                    mbar_wait(BAR_SFULLC + (c - 2) * 8, 0);
                    if (c == 2) prefetch_l2((const char*)ws + blockIdx.x * kWShare, kWShare);
                    load_s_chunk(maps, row0, c, pol_x);
                }
            }
            const int w = warp - 9;
            const int rw = row0 + w * 64;
            const uint32_t stg = STG + w * kWgStride;
            const uint32_t stgfull = BAR_STGFULL + w * 8;
            mbar_wait(BAR_TAB, 0);
            mbar_wait(BAR_SFULLC + (kNSC - 1) * 8, 0);
            uint32_t pub = 0;
#pragma unroll 1
            for (uint32_t t = 0; t < (uint32_t)kTiles; ++t) {
                const uint32_t e = lds32x<SCHED + 4 * kMaxRing>(t * 4);
                const uint32_t c0 = e & 15, one = (e >> 4) & 1, l = (e >> 12) & 3;
                mbar_expect_tx(stgfull, ((e & T_BIAS) ? (256u >> one) : 0u) + ((e & T_X0) ? (16384u >> one) : 0u) +
                                            ((e & T_XB) ? 512u : 0u));
                if (e & T_BIAS) bulk_load(BIAS + w * kBiasStride, bs + l * kD + c0 * 64, 256u >> one, stgfull);
                if (e & T_XB) bulk_load(BIAS + w * kBiasStride + 256, bs, 512, stgfull);
                if (e & T_X0) tma_load(stg, &maps.m[M_X0_T2 + one], rw, c0, stgfull, t == 0 ? pol_n : pol_x);
                bulk_wait0();
                if (pub) {
                    fence_proxy_async_global();
                    mbar_arrive(BAR_XREADY - 8 + pub * 8);
                }
                pub = (e >> 8) & 7;
                if (e & T_SREL) {
                    mbar_wait(BAR_SFREE + w * 8, l & 1);
                    mbar_expect_tx(BAR_SFULL + w * 8, kNSC * 8192);
#pragma unroll 1
                    for (int c = 0; c < kNSC; ++c) {
                        tma_load(SREG + w * kWgStride + c * 8192, &maps.m[M_OUT_T1], rw, c, BAR_SFULL + w * 8, pol_n);
                        if (c < kNSC - 1) __nanosleep(500);
                    }
                }
                mbar_wait(BAR_OUTRDY + w * 8, t & 1);
                if (e & T_STORE) {
                    tma_store(&maps.m[M_OUT_T2 + one], rw, c0, stg, l == kL - 1 ? pol_x : pol_n);
                    bulk_commit();
                    bulk_wait_read0();
                }
            }
        }
    } else {
        asm volatile("setmaxnreg.inc.sync.aligned.u32 240;");
        Ctx cx;
        cx.it = 0;
        set_pass(cx, 0);
        cx.wg = warp >> 2;
        cx.lane0 = (lane == 0);
        cx.tcnt = 0;
        {
            const int r = (warp & 3) * 16 + (lane & 7) + ((lane >> 3) & 1) * 8;
            cx.tb = r * 128 + (((lane >> 4) ^ (lane & 7)) * 16) + cx.wg * kWgStride;
            cx.bb = (lane >> 3) * 16 + cx.wg * kBiasStride;
        }
        uint32_t a[kNRC][16];
        float acc[64];
        {
            float accB[64], accC[64];
            fused_pass(cx, acc, accB, accC);
            do_tile<7>(cx, a, acc, 0, accB, accC);
        }
        int l = 0;
#pragma unroll 1
        while (true) {
            do_tile<4>(cx, a, acc, l, acc, acc);
            do_tile<5>(cx, a, acc, l, acc, acc);
            do_tile<6>(cx, a, acc, l, acc, acc);
            if (++l == kL) break;
            do_tile<0>(cx, a, acc, l, acc, acc);
            do_tile<1>(cx, a, acc, l, acc, acc);
            do_tile<2>(cx, a, acc, l, acc, acc);
            do_tile<3>(cx, a, acc, l, acc, acc);
            set_pass(cx, l);
        }
        publish_stage(cx);
    }
}

typedef CUresult (*EncodeFn)(CUtensorMap*, CUtensorMapDataType, cuuint32_t, void*, const cuuint64_t*,
                             const cuuint64_t*, const cuuint32_t*, const cuuint32_t*, CUtensorMapInterleave,
                             CUtensorMapSwizzle, CUtensorMapL2promotion, CUtensorMapFloatOOBfill);

bool encode3d(EncodeFn fn, CUtensorMap* tm, const void* ptr, uint64_t rows, uint32_t brows, uint32_t batoms) {
    cuuint64_t dims[3] = {64, rows, 13};
    cuuint64_t strides[2] = {kD * 2, 128};
    cuuint32_t box[3] = {64, brows, batoms};
    cuuint32_t es[3] = {1, 1, 1};
    return fn(tm, CU_TENSOR_MAP_DATA_TYPE_BFLOAT16, 3, const_cast<void*>(ptr), dims, strides, box, es,
              CU_TENSOR_MAP_INTERLEAVE_NONE, CU_TENSOR_MAP_SWIZZLE_128B, CU_TENSOR_MAP_L2_PROMOTION_L2_128B,
              CU_TENSOR_MAP_FLOAT_OOB_FILL_NONE) == CUDA_SUCCESS;
}

}

extern "C" void kernel_launch(void* const* d_in, const int* in_sizes, int n_in, void* d_out, int out_size) {
    (void)in_sizes; (void)n_in; (void)out_size;
    static EncodeFn fn = nullptr;
    if (!fn) {
        void* p = nullptr;
        cudaDriverEntryPointQueryResult qr;
        cudaGetDriverEntryPoint("cuTensorMapEncodeTiled", &p, cudaEnableDefault, &qr);
        fn = (EncodeFn)p;
        cudaFuncSetAttribute(dcn_kernel, cudaFuncAttributeMaxDynamicSharedMemorySize, SMEM_BYTES);
    }
    if (!fn) return;
    Maps maps;
    encode3d(fn, &maps.m[M_WK0], d_in[1], (uint64_t)kL * kD, 64, 2);
    encode3d(fn, &maps.m[M_WK1], d_in[1], (uint64_t)kL * kD, 128, 1);
    encode3d(fn, &maps.m[M_WK2], d_in[1], (uint64_t)kL * kD, 64, 1);
    encode3d(fn, &maps.m[M_X0_R128], d_in[0], kB, 128, 1);
    encode3d(fn, &maps.m[M_OUT_R128], d_out, kB, 128, 1);
    encode3d(fn, &maps.m[M_X0_T2], d_in[0], kB, 64, 2);
    encode3d(fn, &maps.m[M_X0_T1], d_in[0], kB, 64, 1);
    encode3d(fn, &maps.m[M_OUT_T2], d_out, kB, 64, 2);
    encode3d(fn, &maps.m[M_OUT_T1], d_out, kB, 64, 1);
    dcn_kernel<<<kB / kBM, 384, SMEM_BYTES>>>(maps, (const __nv_bfloat16*)d_in[2], (const __nv_bfloat16*)d_in[1],
                                              (const __nv_bfloat16*)d_in[0]);
}
```
